```python
import torch

def _softmax(x, axis=-1):
    return torch.softmax(x, dim=axis)
def _gelu(x):
    return torch.nn.functional.gelu(x, approximate="tanh")
def _silu(x):
    return torch.nn.functional.silu(x)
def _sigmoid(x):
    return torch.sigmoid(x)
def _layernorm(x, axis=-1, eps=1e-5):
    m = x.mean(dim=axis, keepdim=True)
    v = x.var(dim=axis, keepdim=True, unbiased=False)
    return (x - m) / torch.sqrt(v + eps)
def _scatter_add(tgt, idx, src, axis=0):
    return tgt.clone().index_add_(axis, idx, src)
def _segment_sum(src, seg, n):
    out = torch.zeros((n,) + src.shape[1:], dtype=src.dtype)
    return out.index_add_(0, seg, src)
def _pad(x, pw):
    flat = tuple(v for pair in reversed(pw) for v in pair)
    return torch.nn.functional.pad(x, flat)

kernel_name = 'standalone__gqa_block_cached__near_ridge'

def setup_inputs():

    _w = (lambda a: (lambda t: t.to(torch.bfloat16) if t.is_floating_point() else t)(torch.as_tensor(a)))
    B, Sq, D = 8, 48, 1024
    Hq, Hkv, Sk, Dh = 32, 4, 2048, 128
    assert Hq % Hkv == 0, (Hq, Hkv)
    return {
        "x": _w((lambda *s: torch.randn(*s, dtype=torch.bfloat16) * 0.8)(B, Sq, D)),
        "k_cache": _w((lambda *s: torch.randn(*s, dtype=torch.bfloat16) * 0.8)(B, Hkv, Sk, Dh)),
        "v_cache": _w((lambda *s: torch.randn(*s, dtype=torch.bfloat16) * 0.05)(B, Hkv, Sk, Dh)),
        "wq": _w((lambda *s: torch.randn(*s, dtype=torch.bfloat16) * 0.8)(D, Hq * Dh) * (D ** -0.5)),
        "wo": _w((lambda *s: torch.randn(*s, dtype=torch.bfloat16) * 0.05)(Hq * Dh, D) * ((Hq * Dh) ** -0.5)),
    }

def reference(x, k_cache, v_cache, wq, wo):
    B, Sq, D = x.shape
    Hq, Dh = 32, 128
    Hkv = k_cache.shape[1]
    rep = Hq // Hkv
    q = (lambda x, *d: x.permute(*d))((x @ wq).reshape(B, Sq, Hq, Dh), 0, 2, 1, 3)
    k = (lambda x, n, axis: torch.repeat_interleave(x, n, dim=axis))(k_cache, rep, axis=1)
    v = (lambda x, n, axis: torch.repeat_interleave(x, n, dim=axis))(v_cache, rep, axis=1)
    scores = torch.einsum("bhqd,bhkd->bhqk", q, k) * (Dh ** -0.5)
    p = _softmax(scores, axis=-1)
    o = torch.einsum("bhqk,bhkd->bhqd", p, v)
    return (lambda x, *d: x.permute(*d))(o, 0, 2, 1, 3).reshape(B, Sq, Hq * Dh) @ wo
```

```cpp
#include <cuda_runtime.h>
#include <cuda_bf16.h>
#include <cuda.h>
#include <stdint.h>

namespace {

constexpr int NCTA = 128;
constexpr int NTHREADS = 512;
constexpr int SLOT = 32768;
constexpr int NSLOT = 5;
constexpr int OFF_ZERO = 0;
constexpr int OFF_ML = 8192;
constexpr int OFF_Q = 14336;
constexpr int OFF_RING = OFF_Q + 49152;
constexpr int OFF_BAR = OFF_RING + NSLOT * SLOT;
constexpr int SMEM_BYTES = OFF_BAR + 512;
constexpr int BAR_FULL = 0, BAR_EMPTY = 5, BAR_XFREE = 10, BAR_QARR = 13, BAR_CDONE = 14, BAR_EMPTY3 = 15, BAR_ONES = 20,
              BAR_XFULL = 20, BAR_QFULL = 23, BAR_TMP = 26, BAR_TMP2 = 29, BAR_STAGEFREE = 32, BAR_GO2 = 33, BAR_EPOCH = 34,
              BAR_BOK = 35, BAR_GRP = 36, BAR_FULL3 = 39, BAR_OFULL = 44, BAR_WFULL = 49, BAR_END = 59;
constexpr int OFF_ZT = OFF_BAR + BAR_END * 8;

constexpr unsigned B_CNT = 64;
constexpr uint32_t QPAR_BYTES = 64 * 49152;
#define PF_WO_START 20000
#define PF_WO_INTERVAL 1200
#define KV_EARLY 2
#define SCHED 3
#define PROBE_DELAY 500
#define H_KV_N 3
#define H_START 1500
#define H_KV_INT 0
#define H_WO_START 14000
#define H_WO_INT 750
#define ARR_CH 0
#define SKEW3 0
#define WSPACE 2
#define P1_SOLO 0
#define PRE 1
#define PRE_GAP 0
#define PRE_GAP0 0
#define QARR_LATE 1
#define EXP 0
#define BOTH_T 0
#define CADENCE 0
#define CAD0 1200
#define P3_SOLO 0
#define PF_KV_N 3
#define PF_KV_START 5000
#define PF_KV_INT 250
#define CLR_NS 300
#define GO2_AT 8
#define PLACE 1
constexpr int SPIN_LIMIT = 1 << 22;
constexpr float L_SAFE = 1.0995116e12f;

__device__ uint4 g_qimg[2 * 64 * 49152 / 16];
__device__ uint4 g_oimg[16 * 16 * 12288 / 16];
__device__ unsigned g_bflag[2 * 32];

__device__ __forceinline__ void TL(int) {}
__device__ __forceinline__ void TLP(int, uint32_t, int) {}
#define TLC(idx)
#define TLF(idx)
#define TLPF(c, sb, idx)
#define STALL_BEGIN()
#define STALL_END(idx)
#define TL_INIT()
#define TL_DUMP()
#define TL_DONE()
constexpr int SMEM_TOTAL = SMEM_BYTES;

__device__ __forceinline__ uint32_t smem_u32(const void* p) { return (uint32_t)__cvta_generic_to_shared(p); }
__device__ __forceinline__ void mbar_init(uint32_t bar, uint32_t cnt) {
    asm volatile("mbarrier.init.shared::cta.b64 [%0], %1;" ::"r"(bar), "r"(cnt) : "memory");
}
__device__ __forceinline__ void mbar_expect_tx(uint32_t bar, uint32_t bytes) {
    asm volatile("mbarrier.arrive.expect_tx.shared::cta.b64 _, [%0], %1;" ::"r"(bar), "r"(bytes) : "memory");
}
__device__ __forceinline__ void mbar_arrive(uint32_t bar) {
    asm volatile("mbarrier.arrive.shared::cta.b64 _, [%0];" ::"r"(bar) : "memory");
}
__device__ __forceinline__ void mbar_arrive_cnt(uint32_t bar, uint32_t cnt) {
    asm volatile("mbarrier.arrive.shared::cta.b64 _, [%0], %1;" ::"r"(bar), "r"(cnt) : "memory");
}
__device__ __forceinline__ void mbar_arrive_remote(uint32_t cluster_addr) {
    asm volatile("fence.release.sync_restrict::shared::cta.cluster;\n"
                 "mbarrier.arrive.relaxed.cluster.shared::cluster.b64 _, [%0];" ::"r"(cluster_addr) : "memory");
}
__device__ __forceinline__ void (mbar_wait)(uint32_t bar, uint32_t parity) {
    asm volatile(
        "{\n.reg .pred p, q;\n.reg .u32 c;\nmov.u32 c, 0;\n"
        "WAIT_LOOP:\n"
        "mbarrier.try_wait.parity.shared::cta.b64 p, [%0], %1;\n"
        "@p bra WAIT_DONE;\n"
        "add.u32 c, c, 1;\nsetp.gt.u32 q, c, %2;\n@q trap;\n"
        "bra WAIT_LOOP;\n"
        "WAIT_DONE:\n}\n" ::"r"(bar), "r"(parity), "n"(SPIN_LIMIT) : "memory");
}
__device__ __forceinline__ void (mbar_wait_cluster)(uint32_t bar, uint32_t parity) {
    asm volatile(
        "{\n.reg .pred p, q;\n.reg .u32 c;\nmov.u32 c, 0;\n"
        "WAIT_LOOP:\n"
        "mbarrier.try_wait.parity.acquire.cluster.shared::cta.b64 p, [%0], %1;\n"
        "@p bra WAIT_DONE;\n"
        "add.u32 c, c, 1;\nsetp.gt.u32 q, c, %2;\n@q trap;\n"
        "bra WAIT_LOOP;\n"
        "WAIT_DONE:\n}\n" ::"r"(bar), "r"(parity), "n"(SPIN_LIMIT) : "memory");
}
__device__ __forceinline__ bool elect_one() {
    uint32_t el;
    asm volatile("{\n.reg .pred p;\nelect.sync _|p, 0xffffffff;\nselp.u32 %0, 1, 0, p;\n}" : "=r"(el));
    return el != 0;
}
__device__ __forceinline__ void prefetch_tmap(const CUtensorMap* tm) { asm volatile("prefetch.tensormap [%0];" ::"l"(tm) : "memory"); }
__device__ __forceinline__ uint32_t mapa(uint32_t addr, uint32_t rank) {
    uint32_t r;
    asm("mapa.shared::cluster.u32 %0, %1, %2;" : "=r"(r) : "r"(addr), "r"(rank));
    return r;
}
__device__ __forceinline__ void tma_2d(uint32_t dst, const CUtensorMap* tm, int c0, int c1, uint32_t bar) {
    asm volatile("cp.async.bulk.tensor.2d.shared::cluster.global.mbarrier::complete_tx::bytes [%0], [%1, {%3, %4}], [%2];"
                 ::"r"(dst), "l"(tm), "r"(bar), "r"(c0), "r"(c1) : "memory");
}
__device__ __forceinline__ void tma_3d(uint32_t dst, const CUtensorMap* tm, int c0, int c1, int c2, uint32_t bar) {
    asm volatile("cp.async.bulk.tensor.3d.shared::cluster.global.mbarrier::complete_tx::bytes [%0], [%1, {%3, %4, %5}], [%2];"
                 ::"r"(dst), "l"(tm), "r"(bar), "r"(c0), "r"(c1), "r"(c2) : "memory");
}
__device__ __forceinline__ void bulk_g2s(uint32_t dst, const void* src, uint32_t bytes, uint32_t bar) {
    asm volatile("cp.async.bulk.shared::cluster.global.mbarrier::complete_tx::bytes [%0], [%1], %2, [%3];"
                 ::"r"(dst), "l"(src), "r"(bytes), "r"(bar) : "memory");
}
__device__ __forceinline__ void bulk_s2g(void* dst, uint32_t src, uint32_t bytes) {
    asm volatile("cp.async.bulk.global.shared::cta.bulk_group [%0], [%1], %2;" ::"l"(dst), "r"(src), "r"(bytes) : "memory");
}
__device__ __forceinline__ void tma_reduce_add_2d(const CUtensorMap* tm, int c0, int c1, uint32_t src) {
    asm volatile("cp.reduce.async.bulk.tensor.2d.global.shared::cta.add.tile.bulk_group [%0, {%2, %3}], [%1];"
                 ::"l"(tm), "r"(src), "r"(c0), "r"(c1) : "memory");
}
__device__ __forceinline__ void l2_prefetch(const void* src, uint32_t bytes) {
    asm volatile("cp.async.bulk.prefetch.L2.global [%0], %1;" ::"l"(src), "r"(bytes) : "memory");
}
__device__ __forceinline__ uint32_t clock32() {
    uint32_t c;
    asm volatile("mov.u32 %0, %%clock;" : "=r"(c)::"memory");
    return c;
}
__device__ __forceinline__ void bulk_commit() { asm volatile("cp.async.bulk.commit_group;" ::: "memory"); }
__device__ __forceinline__ void bulk_wait0() { asm volatile("cp.async.bulk.wait_group 0;" ::: "memory"); }
__device__ __forceinline__ void bulk_wait0_read() { asm volatile("cp.async.bulk.wait_group.read 0;" ::: "memory"); }
__device__ __forceinline__ void fence_async_smem() { asm volatile("fence.proxy.async.shared::cta;" ::: "memory"); }
__device__ __forceinline__ void fence_async_all() { asm volatile("fence.proxy.async;" ::: "memory"); }
__device__ __forceinline__ void red_release(unsigned* p, unsigned v) {
    asm volatile("red.release.gpu.global.add.u32 [%0], %1;" ::"l"(p), "r"(v) : "memory");
}
__device__ __forceinline__ unsigned ld_acquire(const unsigned* p) {
    unsigned v;
    asm volatile("ld.acquire.gpu.global.u32 %0, [%1];" : "=r"(v) : "l"(p) : "memory");
    return v;
}
__device__ __forceinline__ unsigned ld_relaxed(const unsigned* p) {
    unsigned v;
    asm volatile("ld.relaxed.gpu.global.u32 %0, [%1];" : "=r"(v) : "l"(p) : "memory");
    return v;
}
__device__ __forceinline__ void (flag_wait)(const unsigned* p, unsigned target) {
    asm volatile(
        "{\n.reg .pred p, q;\n.reg .u32 c, v;\nmov.u32 c, 0;\n"
        "FLAG_LOOP:\n"
        "ld.acquire.gpu.global.u32 v, [%0];\n"
        "sub.u32 v, v, %1;\nsetp.ge.s32 p, v, 0;\n"
        "@p bra FLAG_DONE;\n"
        "add.u32 c, c, 1;\nsetp.gt.u32 q, c, %2;\n@q trap;\n"
        "bra FLAG_LOOP;\n"
        "FLAG_DONE:\n}\n" ::"l"(p), "r"(target), "n"(SPIN_LIMIT) : "memory");
}
__device__ __forceinline__ void named_sync(int id) { asm volatile("bar.sync %0, 128;" ::"r"(id) : "memory"); }
__device__ __forceinline__ void wg_fence() { asm volatile("wgmma.fence.sync.aligned;" ::: "memory"); }
__device__ __forceinline__ void wg_commit() { asm volatile("wgmma.commit_group.sync.aligned;" ::: "memory"); }
template <int N> __device__ __forceinline__ void wg_wait() { asm volatile("wgmma.wait_group.sync.aligned %0;" ::"n"(N) : "memory"); }
template <int N> __device__ __forceinline__ void reg_fence(float (&d)[N]) {
#pragma unroll
    for (int i = 0; i < N; i++) asm volatile("" : "+f"(d[i])::"memory");
}
__device__ __forceinline__ uint64_t mkdesc(uint32_t addr, uint32_t lbo, uint32_t sbo) {
    return (uint64_t)((addr & 0x3FFFF) >> 4) | ((uint64_t)(lbo >> 4) << 16) | ((uint64_t)(sbo >> 4) << 32) | (1ull << 62);
}
__device__ __forceinline__ uint32_t pack_bf16(float lo, float hi) {
    uint32_t r;
    asm("cvt.rn.bf16x2.f32 %0, %1, %2;" : "=r"(r) : "f"(hi), "f"(lo));
    return r;
}
__device__ __forceinline__ uint32_t hadd2(uint32_t a, uint32_t b) {
    uint32_t r;
    asm("add.rn.bf16x2 %0, %1, %2;" : "=r"(r) : "r"(a), "r"(b));
    return r;
}
__device__ __forceinline__ float ex2(float x) {
    float y;
    asm("ex2.approx.ftz.f32 %0, %1;" : "=f"(y) : "f"(x));
    return y;
}
__device__ __forceinline__ void stsm_x4(uint32_t addr, uint32_t r0, uint32_t r1, uint32_t r2, uint32_t r3) {
    asm volatile("stmatrix.sync.aligned.m8n8.x4.shared.b16 [%0], {%1, %2, %3, %4};" ::"r"(addr), "r"(r0), "r"(r1), "r"(r2), "r"(r3) : "memory");
}
__device__ __forceinline__ void stsm_x4_t(uint32_t addr, uint32_t r0, uint32_t r1, uint32_t r2, uint32_t r3) {
    asm volatile("stmatrix.sync.aligned.m8n8.x4.trans.shared.b16 [%0], {%1, %2, %3, %4};" ::"r"(addr), "r"(r0), "r"(r1), "r"(r2), "r"(r3) : "memory");
}
__device__ __forceinline__ void st_async_v4(uint32_t addr, float a, float b, float c, float d, uint32_t bar) {
    asm volatile("st.async.weak.shared::cluster.mbarrier::complete_tx::bytes.v4.f32 [%0], {%1, %2, %3, %4}, [%5];"
                 ::"r"(addr), "f"(a), "f"(b), "f"(c), "f"(d), "r"(bar) : "memory");
}
__device__ __forceinline__ void st_async_v4u(uint32_t addr, uint32_t a, uint32_t b, uint32_t c, uint32_t d, uint32_t bar) {
    asm volatile("st.async.weak.shared::cluster.mbarrier::complete_tx::bytes.v4.b32 [%0], {%1, %2, %3, %4}, [%5];"
                 ::"r"(addr), "r"(a), "r"(b), "r"(c), "r"(d), "r"(bar) : "memory");
}
__device__ __forceinline__ uint32_t lds_u32(uint32_t addr) {
    uint32_t v;
    asm volatile("ld.shared.u32 %0, [%1];" : "=r"(v) : "r"(addr) : "memory");
    return v;
}
__device__ __forceinline__ float rcp_fast(float x) {
    float y;
    asm("rcp.approx.ftz.f32 %0, %1;" : "=f"(y) : "f"(x));
    return y;
}
__device__ __forceinline__ float bf_lo(uint32_t w) { return __uint_as_float(w << 16); }
__device__ __forceinline__ float bf_hi(uint32_t w) { return __uint_as_float(w & 0xffff0000u); }
__device__ __forceinline__ float4 lds_v4(uint32_t addr) {
    float4 v;
    asm volatile("ld.shared.v4.f32 {%0, %1, %2, %3}, [%4];" : "=f"(v.x), "=f"(v.y), "=f"(v.z), "=f"(v.w) : "r"(addr) : "memory");
    return v;
}

__device__ __forceinline__ uint4 ld_relaxed_v4(const void* p) {
    uint4 v;
    asm volatile("ld.relaxed.gpu.global.v4.u32 {%0, %1, %2, %3}, [%4];" : "=r"(v.x), "=r"(v.y), "=r"(v.z), "=r"(v.w) : "l"(p) : "memory");
    return v;
}
__device__ __forceinline__ void st_relaxed_v4(void* p, uint32_t a, uint32_t b, uint32_t c, uint32_t d) {
    asm volatile("st.relaxed.gpu.global.v4.u32 [%0], {%1, %2, %3, %4};" ::"l"(p), "r"(a), "r"(b), "r"(c), "r"(d) : "memory");
}
__device__ __forceinline__ uint32_t pack_nz(float lo, float hi) {
    const uint32_t w = pack_bf16(lo, hi);
    return w == 0u ? 0x80008000u : w;
}
__device__ __forceinline__ bool valid4(const uint4& v) { return min(min(v.x, v.y), min(v.z, v.w)) != 0u; }
__device__ __forceinline__ void (probe_wait)(const void* p) {
    asm volatile(
        "{\n.reg .pred p, q;\n.reg .u32 c, v;\nmov.u32 c, 0;\n"
        "PROBE_LOOP:\n"
        "ld.relaxed.gpu.global.u32 v, [%0];\n"
        "setp.ne.u32 p, v, 0;\n"
        "vote.sync.all.pred p, p, 0xffffffff;\n"
        "@p bra PROBE_DONE;\n"
        "add.u32 c, c, 1;\nsetp.gt.u32 q, c, %1;\n@q trap;\n"
        "bra PROBE_LOOP;\n"
        "PROBE_DONE:\n}\n" ::"l"(p), "n"(SPIN_LIMIT) : "memory");
}
__device__ __forceinline__ void bar_sync_n(int id, int n) { asm volatile("bar.sync %0, %1;" ::"r"(id), "r"(n) : "memory"); }
__device__ __forceinline__ void bar_arrive_n(int id, int n) { asm volatile("bar.arrive %0, %1;" ::"r"(id), "r"(n) : "memory"); }
__device__ __forceinline__ uint32_t movm_t(uint32_t a) {
    uint32_t d;
    asm volatile("movmatrix.sync.aligned.m8n8.trans.b16 %0, %1;" : "=r"(d) : "r"(a));
    return d;
}
__device__ __forceinline__ void mma_16816(float* d, uint32_t a0, uint32_t a1, uint32_t a2, uint32_t a3, uint32_t b0, uint32_t b1) {
    asm volatile("mma.sync.aligned.m16n8k16.row.col.f32.bf16.bf16.f32 {%0, %1, %2, %3}, {%4, %5, %6, %7}, {%8, %9}, {%0, %1, %2, %3};"
                 : "+f"(d[0]), "+f"(d[1]), "+f"(d[2]), "+f"(d[3]) : "r"(a0), "r"(a1), "r"(a2), "r"(a3), "r"(b0), "r"(b1));
}

template <int TA, int TB>
__device__ __forceinline__ void wgmma_n96_ss(float (&d)[48], uint64_t da, uint64_t db, int scale_d) {
    asm volatile("{\n.reg .pred p;\nsetp.ne.b32 p, %50, 0;\n"
        "wgmma.mma_async.sync.aligned.m64n96k16.f32.bf16.bf16 {"
        "%0, %1, %2, %3, %4, %5, %6, %7, %8, %9, %10, %11, %12, %13, %14, %15, "
        "%16, %17, %18, %19, %20, %21, %22, %23, %24, %25, %26, %27, %28, %29, %30, %31, "
        "%32, %33, %34, %35, %36, %37, %38, %39, %40, %41, %42, %43, %44, %45, %46, %47}, "
        "%48, %49, p, 1, 1, %51, %52;\n}\n"
        : "+f"(d[0]), "+f"(d[1]), "+f"(d[2]), "+f"(d[3]), "+f"(d[4]), "+f"(d[5]), "+f"(d[6]), "+f"(d[7]),
          "+f"(d[8]), "+f"(d[9]), "+f"(d[10]), "+f"(d[11]), "+f"(d[12]), "+f"(d[13]), "+f"(d[14]), "+f"(d[15]),
          "+f"(d[16]), "+f"(d[17]), "+f"(d[18]), "+f"(d[19]), "+f"(d[20]), "+f"(d[21]), "+f"(d[22]), "+f"(d[23]),
          "+f"(d[24]), "+f"(d[25]), "+f"(d[26]), "+f"(d[27]), "+f"(d[28]), "+f"(d[29]), "+f"(d[30]), "+f"(d[31]),
          "+f"(d[32]), "+f"(d[33]), "+f"(d[34]), "+f"(d[35]), "+f"(d[36]), "+f"(d[37]), "+f"(d[38]), "+f"(d[39]),
          "+f"(d[40]), "+f"(d[41]), "+f"(d[42]), "+f"(d[43]), "+f"(d[44]), "+f"(d[45]), "+f"(d[46]), "+f"(d[47])
        : "l"(da), "l"(db), "r"(scale_d), "n"(TA), "n"(TB));
}
template <int TA, int TB>
__device__ __forceinline__ void wgmma_n128_ss(float (&d)[64], uint64_t da, uint64_t db, int scale_d) {
    asm volatile("{\n.reg .pred p;\nsetp.ne.b32 p, %66, 0;\n"
        "wgmma.mma_async.sync.aligned.m64n128k16.f32.bf16.bf16 {"
        "%0, %1, %2, %3, %4, %5, %6, %7, %8, %9, %10, %11, %12, %13, %14, %15, "
        "%16, %17, %18, %19, %20, %21, %22, %23, %24, %25, %26, %27, %28, %29, %30, %31, "
        "%32, %33, %34, %35, %36, %37, %38, %39, %40, %41, %42, %43, %44, %45, %46, %47, "
        "%48, %49, %50, %51, %52, %53, %54, %55, %56, %57, %58, %59, %60, %61, %62, %63}, "
        "%64, %65, p, 1, 1, %67, %68;\n}\n"
        : "+f"(d[0]), "+f"(d[1]), "+f"(d[2]), "+f"(d[3]), "+f"(d[4]), "+f"(d[5]), "+f"(d[6]), "+f"(d[7]),
          "+f"(d[8]), "+f"(d[9]), "+f"(d[10]), "+f"(d[11]), "+f"(d[12]), "+f"(d[13]), "+f"(d[14]), "+f"(d[15]),
          "+f"(d[16]), "+f"(d[17]), "+f"(d[18]), "+f"(d[19]), "+f"(d[20]), "+f"(d[21]), "+f"(d[22]), "+f"(d[23]),
          "+f"(d[24]), "+f"(d[25]), "+f"(d[26]), "+f"(d[27]), "+f"(d[28]), "+f"(d[29]), "+f"(d[30]), "+f"(d[31]),
          "+f"(d[32]), "+f"(d[33]), "+f"(d[34]), "+f"(d[35]), "+f"(d[36]), "+f"(d[37]), "+f"(d[38]), "+f"(d[39]),
          "+f"(d[40]), "+f"(d[41]), "+f"(d[42]), "+f"(d[43]), "+f"(d[44]), "+f"(d[45]), "+f"(d[46]), "+f"(d[47]),
          "+f"(d[48]), "+f"(d[49]), "+f"(d[50]), "+f"(d[51]), "+f"(d[52]), "+f"(d[53]), "+f"(d[54]), "+f"(d[55]),
          "+f"(d[56]), "+f"(d[57]), "+f"(d[58]), "+f"(d[59]), "+f"(d[60]), "+f"(d[61]), "+f"(d[62]), "+f"(d[63])
        : "l"(da), "l"(db), "r"(scale_d), "n"(TA), "n"(TB));
}
template <int TB>
__device__ __forceinline__ void wgmma_n128_rs(float (&d)[64], uint32_t a0, uint32_t a1, uint32_t a2, uint32_t a3, uint64_t db, int scale_d) {
    asm volatile("{\n.reg .pred p;\nsetp.ne.b32 p, %69, 0;\n"
        "wgmma.mma_async.sync.aligned.m64n128k16.f32.bf16.bf16 {"
        "%0, %1, %2, %3, %4, %5, %6, %7, %8, %9, %10, %11, %12, %13, %14, %15, "
        "%16, %17, %18, %19, %20, %21, %22, %23, %24, %25, %26, %27, %28, %29, %30, %31, "
        "%32, %33, %34, %35, %36, %37, %38, %39, %40, %41, %42, %43, %44, %45, %46, %47, "
        "%48, %49, %50, %51, %52, %53, %54, %55, %56, %57, %58, %59, %60, %61, %62, %63}, "
        "{%64, %65, %66, %67}, %68, p, 1, 1, %70;\n}\n"
        : "+f"(d[0]), "+f"(d[1]), "+f"(d[2]), "+f"(d[3]), "+f"(d[4]), "+f"(d[5]), "+f"(d[6]), "+f"(d[7]),
          "+f"(d[8]), "+f"(d[9]), "+f"(d[10]), "+f"(d[11]), "+f"(d[12]), "+f"(d[13]), "+f"(d[14]), "+f"(d[15]),
          "+f"(d[16]), "+f"(d[17]), "+f"(d[18]), "+f"(d[19]), "+f"(d[20]), "+f"(d[21]), "+f"(d[22]), "+f"(d[23]),
          "+f"(d[24]), "+f"(d[25]), "+f"(d[26]), "+f"(d[27]), "+f"(d[28]), "+f"(d[29]), "+f"(d[30]), "+f"(d[31]),
          "+f"(d[32]), "+f"(d[33]), "+f"(d[34]), "+f"(d[35]), "+f"(d[36]), "+f"(d[37]), "+f"(d[38]), "+f"(d[39]),
          "+f"(d[40]), "+f"(d[41]), "+f"(d[42]), "+f"(d[43]), "+f"(d[44]), "+f"(d[45]), "+f"(d[46]), "+f"(d[47]),
          "+f"(d[48]), "+f"(d[49]), "+f"(d[50]), "+f"(d[51]), "+f"(d[52]), "+f"(d[53]), "+f"(d[54]), "+f"(d[55]),
          "+f"(d[56]), "+f"(d[57]), "+f"(d[58]), "+f"(d[59]), "+f"(d[60]), "+f"(d[61]), "+f"(d[62]), "+f"(d[63])
        : "r"(a0), "r"(a1), "r"(a2), "r"(a3), "l"(db), "r"(scale_d), "n"(TB));
}

template <bool P3>
__device__ __forceinline__ void proj_mainloop(float (&acc)[48], uint32_t sb, int half, int lane) {
    constexpr int F0 = P3 ? 32 : 0;
    int slot = F0 % NSLOT, par = (F0 / NSLOT) & 1, opar = 0;
    int prev = 0;
#pragma unroll 1
    for (int kb = 0; kb < 16; kb++) {
        mbar_wait(sb + OFF_BAR + (BAR_FULL + slot) * 8, par);
        if (P3) mbar_wait(sb + OFF_BAR + (BAR_OFULL + slot) * 8, opar);
        const uint32_t st = __shfl_sync(0xffffffffu, sb + OFF_RING + slot * SLOT, 0);
        const uint64_t da = mkdesc(st + half * 8192, 0, 1024);
        const uint64_t db = mkdesc(st + 16384, 0, 1024);
        wg_fence();
#pragma unroll
        for (int kk = 0; kk < 4; kk++) wgmma_n96_ss<1, 0>(acc, da + kk * (2048 >> 4), db + kk * (32 >> 4), (kb | kk) != 0);
        wg_commit();
        if (threadIdx.x == 128 && (kb & 1) == 0) TL((P3 ? 56 : 48) + kb / 2);
        if (kb > 0) {
            wg_wait<1>();
            if (lane == 0) mbar_arrive_cnt(sb + OFF_BAR + (BAR_EMPTY + prev) * 8, 2 - half);
        }
        prev = slot;
        if (++slot == NSLOT) { slot = 0; par ^= 1; }
        if (slot == F0 % NSLOT) opar ^= 1;
    }
    wg_wait<0>();
    reg_fence(acc);
    if (lane == 0) mbar_arrive_cnt(sb + OFF_BAR + (BAR_EMPTY + prev) * 8, 2 - half);
}

__device__ __noinline__ void attention_fallback(float* o, float* ml, const char* qsrc, const char* kptr, const char* vptr, float c) {
    const int lane = threadIdx.x & 31;
    uint32_t q[32];
#pragma unroll
    for (int i = 0; i < 8; i++) {
        const uint4 v = ld_relaxed_v4(qsrc + i * 512);
        q[4 * i] = movm_t(v.x); q[4 * i + 2] = movm_t(v.y); q[4 * i + 1] = movm_t(v.z); q[4 * i + 3] = movm_t(v.w);
    }
    float acc[64];
#pragma unroll
    for (int i = 0; i < 64; i++) acc[i] = 0.f;
    float m0 = -INFINITY, m1 = -INFINITY, l0 = 0.f, l1 = 0.f;
#pragma unroll 1
    for (int k0 = 0; k0 < 1024; k0 += 16) {
        float sc[8];
#pragma unroll
        for (int i = 0; i < 8; i++) sc[i] = 0.f;
#pragma unroll
        for (int nb = 0; nb < 2; nb++)
#pragma unroll
            for (int kk = 0; kk < 8; kk++) {
                const char* kp = kptr + (size_t)(k0 + nb * 8 + (lane >> 2)) * 256 + kk * 32 + (lane & 3) * 4;
                mma_16816(sc + 4 * nb, q[4 * kk], q[4 * kk + 1], q[4 * kk + 2], q[4 * kk + 3], *(const uint32_t*)kp, *(const uint32_t*)(kp + 16));
            }
        float n0 = fmaxf(fmaxf(sc[0], sc[1]), fmaxf(sc[4], sc[5])) * c, n1 = fmaxf(fmaxf(sc[2], sc[3]), fmaxf(sc[6], sc[7])) * c;
        n0 = fmaxf(n0, __shfl_xor_sync(0xffffffffu, n0, 1)); n1 = fmaxf(n1, __shfl_xor_sync(0xffffffffu, n1, 1));
        n0 = fmaxf(n0, __shfl_xor_sync(0xffffffffu, n0, 2)); n1 = fmaxf(n1, __shfl_xor_sync(0xffffffffu, n1, 2));
        n0 = fmaxf(n0, m0); n1 = fmaxf(n1, m1);
        const float al0 = ex2(m0 - n0), al1 = ex2(m1 - n1);
        m0 = n0; m1 = n1;
        float e[8];
#pragma unroll
        for (int i = 0; i < 8; i++) e[i] = ex2(fmaf(sc[i], c, (i & 2) ? -n1 : -n0));
        l0 = l0 * al0 + (e[0] + e[1]) + (e[4] + e[5]);
        l1 = l1 * al1 + (e[2] + e[3]) + (e[6] + e[7]);
        const uint32_t p0 = pack_bf16(e[0], e[1]), p1 = pack_bf16(e[2], e[3]), p2 = pack_bf16(e[4], e[5]), p3 = pack_bf16(e[6], e[7]);
#pragma unroll
        for (int nb = 0; nb < 16; nb++) {
            const unsigned short* vp = (const unsigned short*)(vptr + (size_t)(k0 + (lane & 3) * 2) * 256) + nb * 8 + (lane >> 2);
            const uint32_t b0 = vp[0] | ((uint32_t)vp[128] << 16), b1 = vp[8 * 128] | ((uint32_t)vp[9 * 128] << 16);
            acc[4 * nb] *= al0; acc[4 * nb + 1] *= al0; acc[4 * nb + 2] *= al1; acc[4 * nb + 3] *= al1;
            mma_16816(acc + 4 * nb, p0, p1, p2, p3, b0, b1);
        }
    }
#pragma unroll
    for (int i = 0; i < 64; i++) o[i] = acc[i];
    ml[0] = m0; ml[1] = m1; ml[2] = l0; ml[3] = l1;
}

template <int S>
__device__ __forceinline__ void combine_and_store(float (&o)[64], float m0, float m1, float l0, float l1, uint32_t sb,
                                                  int wg, int warp, int lane, int tid, char* odst) {
    constexpr int KEEP = S * 32, SEND = 32 - KEEP;
    const uint32_t wbuf = sb + OFF_Q + wg * 16384 + warp * 4096;
    const uint32_t peer_buf = mapa(wbuf + lane * 16, S ^ 1);
    const uint32_t peer_ml = mapa(sb + OFF_ML + tid * 16, S ^ 1);
    const uint32_t peer_bar = mapa(sb + OFF_BAR + (BAR_XFULL + wg) * 8, S ^ 1);
    mbar_wait_cluster(sb + OFF_BAR + (BAR_XFREE + wg) * 8, 0);
    st_async_v4(peer_ml, m0, m1, l0, l1, peer_bar);
#pragma unroll
    for (int i = 0; i < 8; i++)
        st_async_v4(peer_buf + i * 512, o[SEND + 4 * i], o[SEND + 4 * i + 1], o[SEND + 4 * i + 2], o[SEND + 4 * i + 3], peer_bar);
    mbar_wait_cluster(sb + OFF_BAR + (BAR_XFULL + wg) * 8, 0);
    const float4 pml = lds_v4(sb + OFF_ML + tid * 16);
    const float mm0 = fmaxf(m0, pml.x), mm1 = fmaxf(m1, pml.y);
    float a0 = ex2(m0 - mm0), b0 = ex2(pml.x - mm0);
    float a1 = ex2(m1 - mm1), b1 = ex2(pml.y - mm1);
    const float inv0 = 1.0f / (a0 * l0 + b0 * pml.z), inv1 = 1.0f / (a1 * l1 + b1 * pml.w);
    a0 *= inv0; b0 *= inv0; a1 *= inv1; b1 *= inv1;
#pragma unroll
    for (int q = 0; q < 4; q++) {
        const float4 v = lds_v4(wbuf + lane * 16 + (2 * q) * 512), w = lds_v4(wbuf + lane * 16 + (2 * q + 1) * 512);
        const int i = KEEP + 8 * q;
        st_relaxed_v4(odst + q * 512, pack_nz(o[i] * a0 + v.x * b0, o[i + 1] * a0 + v.y * b0), pack_nz(o[i + 2] * a1 + v.z * b1, o[i + 3] * a1 + v.w * b1),
                      pack_nz(o[i + 4] * a0 + w.x * b0, o[i + 5] * a0 + w.y * b0), pack_nz(o[i + 6] * a1 + w.z * b1, o[i + 7] * a1 + w.w * b1));
    }
}

__device__ __forceinline__ int p3_kblock(int n) { return (n >> 2) * 2 + (n & 1) + ((n >> 1) & 1) * 8; }

__global__ void __cluster_dims__(2, 1, 1) __launch_bounds__(NTHREADS, 1)
gqa_fused_kernel(const __grid_constant__ CUtensorMap tm_x, const __grid_constant__ CUtensorMap tm_wq,
                 const __grid_constant__ CUtensorMap tm_k, const __grid_constant__ CUtensorMap tm_v,
                 const __grid_constant__ CUtensorMap tm_wo, const __grid_constant__ CUtensorMap tm_out,
                 __nv_bfloat16* __restrict__ out, const char* __restrict__ wq, const char* __restrict__ kc,
                 const char* __restrict__ vc, const char* __restrict__ wo) {
    extern __shared__ __align__(1024) unsigned char smem[];
    uint32_t sb = smem_u32(smem);
    asm volatile("mov.u32 %0, %0;" : "+r"(sb));
    const int tid = threadIdx.x, lane = tid & 31;
    const int wg = __shfl_sync(0xffffffffu, tid >> 7, 0), warp = __shfl_sync(0xffffffffu, (tid >> 5) & 3, 0);
    const int bid = blockIdx.x;
    const int mem = bid & 3, r = (bid >> 2) & 1, t = (bid >> 3) & 3, g = bid >> 5;
    const int s = mem & 1, b = 2 * t + (mem >> 1), col = bid & 7;
    const int head = g * 8 + r * 4 + mem;

    TL_INIT();
    if (wg == 3 && warp == 0) {
        if (elect_one()) {
            TL(0);
#pragma unroll
            for (int i = 0; i < NSLOT; i++) {
                mbar_init(sb + OFF_BAR + (BAR_FULL + i) * 8, 1);
                mbar_init(sb + OFF_BAR + (BAR_EMPTY + i) * 8, 12);
                mbar_init(sb + OFF_BAR + (BAR_OFULL + i) * 8, 4);
            }
#pragma unroll
            for (int i = 0; i < 3; i++) {
                mbar_init(sb + OFF_BAR + (BAR_XFREE + i) * 8, 4);
                mbar_init(sb + OFF_BAR + (BAR_XFULL + i) * 8, 1);
            }
            mbar_init(sb + OFF_BAR + BAR_GO2 * 8, 1);
            mbar_init(sb + OFF_BAR + (BAR_GO2 + 1) * 8, 1);
            mbar_init(sb + OFF_BAR + (BAR_GO2 + 2) * 8, 12);
            mbar_init(sb + OFF_BAR + (BAR_GO2 + 3) * 8, 1);
            asm volatile("fence.mbarrier_init.release.cluster;" ::: "memory");
            fence_async_smem();
#pragma unroll
            for (int f = 0; f < NSLOT; f++) {
                const uint32_t full = sb + OFF_BAR + (BAR_FULL + f) * 8, st = sb + OFF_RING + f * SLOT;
                mbar_expect_tx(full, 28672);
                tma_3d(st, &tm_wq, 0, f * 64, head * 2, full);
                tma_2d(st + 16384, &tm_x, f * 64, t * 96, full);
            }
#pragma unroll
            for (int f = NSLOT; f < NSLOT + PF_DIST; f++) l2_prefetch(wq + (size_t)f * 524288 + bid * 4096, 4096);
            TL(1);
        }
    } else if (wg == 3 && warp == 1) {
        if (elect_one()) { prefetch_tmap(&tm_k); prefetch_tmap(&tm_v); prefetch_tmap(&tm_wo); prefetch_tmap(&tm_out); }
    }
    __syncthreads();
    asm volatile("barrier.cluster.arrive.relaxed.aligned;" ::: "memory");

    if (wg == 3) {
        asm volatile("setmaxnreg.dec.sync.aligned.u32 32;");
        if (warp == 0) {
            if (elect_one()) {
                uint32_t bar = sb + OFF_BAR, st = sb + OFF_RING;
                uint32_t par = 0;
                auto advance = [&]() {
                    bar += 8; st += SLOT;
                    if (bar == sb + OFF_BAR + NSLOT * 8) { bar = sb + OFF_BAR; st = sb + OFF_RING; par ^= 1; }
                };
#pragma unroll 1
                for (int f = NSLOT; f < 16; f++) {
                    if (f == 15) {
                        mbar_wait(sb + OFF_BAR + (BAR_GO2 + 1) * 8, 0);
                        unsigned at;
                        asm volatile("ld.shared.u32 %0, [%1];" : "=r"(at) : "r"(sb + OFF_ZT) : "memory");
                        flag_wait(g_aflag + (bid >> 2) * 32, at);
                        mbar_arrive(sb + OFF_BAR + (BAR_GO2 + 3) * 8);
                    }
                    mbar_wait(bar + BAR_EMPTY * 8, par);
                    mbar_expect_tx(bar, 28672);
                    tma_3d(st, &tm_wq, 0, f * 64, head * 2, bar);
                    tma_2d(st + 16384, &tm_x, f * 64, t * 96, bar);
                    if (f + PF_DIST < 16) l2_prefetch(wq + (size_t)(f + PF_DIST) * 524288 + bid * 4096, 4096);
                    advance();
                }
                const int kvrow = (b * 4 + g) * 2048 + s * 1024;
                TL(2);
#pragma unroll 1
                for (int f = 0; f < 16; f++) {
                    if (f == KV_EARLY) { mbar_wait(sb + OFF_BAR + (BAR_GO2 + 2) * 8, 0); TL(3); }
                    if (f == 8) mbar_arrive(sb + OFF_BAR + BAR_GO2 * 8);
                    if (f == 15) {
                        mbar_wait(sb + OFF_BAR + (BAR_GO2 + 1) * 8, 1);
                        unsigned bt;
                        asm volatile("ld.shared.u32 %0, [%1];" : "=r"(bt) : "r"(sb + OFF_ZT + 4) : "memory");
                        flag_wait(g_bflag + t * 32, bt);
                        fence_async_all();
                    }
                    mbar_wait(bar + BAR_EMPTY * 8, par);
                    mbar_expect_tx(bar, 32768);
                    tma_3d(st, (f & 1) ? &tm_v : &tm_k, 0, kvrow + (f >> 1) * 128, 0, bar);
                    TL(16 + f);
                    advance();
                }
#pragma unroll 1
                for (int f = 0; f < 16; f++) {
                    mbar_wait(bar + BAR_EMPTY * 8, par);
                    mbar_expect_tx(bar, 16384);
                    tma_3d(st, &tm_wo, 0, g * 1024 + p3_kblock(f) * 64, col * 2, bar);
                    advance();
                }
                TL(6);
            }
        } else if (warp == 1) {
            if (elect_one()) {
                uint32_t next = clock32() + PF_WO_START;
                mbar_wait(sb + OFF_BAR + (BAR_GO2 + 3) * 8, 0);
                {
                    uint32_t nx = clock32() + PF_KV_DELAY;
                    const size_t kvoff = ((size_t)((b * 4 + g) * 2048 + s * 1024 + r * 64)) * 256;
#pragma unroll 1
                    for (int c = KV_EARLY * (16384 / PF_CH); c < PF_KV_END * (16384 / PF_CH); c++) {
                        const int f = c / (16384 / PF_CH);
                        while ((int)(clock32() - nx) < 0) __nanosleep(40);
                        l2_prefetch(((f & 1) ? vc : kc) + kvoff + (size_t)(f >> 1) * 32768 + (c % (16384 / PF_CH)) * PF_CH, PF_CH);
                        nx += PF_KV_INT;
                    }
                }
#pragma unroll 1
                for (int i = 0; i < 16; i++) {
                    while ((int)(clock32() - next) < 0) __nanosleep(200);
                    l2_prefetch(wo + (size_t)g * 2097152 + (size_t)p3_kblock(i) * 131072 + (bid & 31) * 4096, 4096);
                    next += PF_WO_INTERVAL;
                }
                TL(7);
            }
        } else {
            const int i6 = tid & 63;
            unsigned* aflag = g_aflag + (bid >> 2) * 32;
            unsigned* bflag = g_bflag + t * 32;
            if (i6 == 0) {
                const unsigned av = ld_relaxed(aflag), bv = ld_relaxed(bflag);
                asm volatile("st.shared.v2.u32 [%0], {%1, %2};" ::"r"(sb + OFF_ZT), "r"((av / A_CNT + 1) * A_CNT), "r"((bv / B_CNT + 1) * B_CNT) : "memory");
            }
            uint4* qz = g_qbuf + (size_t)((b * 4 + g) * 2 + r) * 3072 + s * 1536 + i6;
#pragma unroll 1
            for (int k = 0; k < 24; k++) { qz[k * 64] = make_uint4(0, 0, 0, 0); if (CLR_SLEEP) __nanosleep(CLR_SLEEP); }
            bar_sync_n(4, 64);
            if (i6 == 0) { red_release(aflag, 1); mbar_arrive(sb + OFF_BAR + (BAR_GO2 + 1) * 8); }
            mbar_wait(sb + OFF_BAR + BAR_GO2 * 8, 0);
            uint4* oz = g_obuf + (size_t)(g * 4 + t) * 12288 + col * 1536 + i6;
#pragma unroll 1
            for (int k = 0; k < 24; k++) { oz[k * 64] = make_uint4(0, 0, 0, 0); __nanosleep(100); }
#pragma unroll
            for (int k = 0; k < 6; k++) {
                const int e = i6 + k * 64;
                *((uint4*)(out + (size_t)(t * 96 + g * 24 + (e >> 4)) * 1024 + col * 128) + (e & 15)) = make_uint4(0, 0, 0, 0);
            }
            bar_sync_n(4, 64);
            if (i6 == 0) { red_release(bflag, 1); mbar_arrive(sb + OFF_BAR + (BAR_GO2 + 1) * 8); }
        }
        __syncwarp();
        asm volatile("barrier.cluster.wait.aligned;" ::: "memory");
        TL_DUMP();
    } else {
        asm volatile("setmaxnreg.inc.sync.aligned.u32 160;");
        const uint32_t qpiece = sb + OFF_Q + wg * 16384;
        const int mi = lane >> 3;
        if (wg > 0) {
            float acc[48];
            proj_mainloop<false>(acc, sb, wg - 1, lane);
            if (tid == 128) TL(8);
#pragma unroll
            for (int bb = 0; bb < 2; bb++)
#pragma unroll
                for (int v = 0; v < 3; v++) {
                    const int j = 6 * bb + 2 * v;
                    char* dst = (char*)g_qbuf + (size_t)(((2 * t + bb) * 4 + g) * 2 + r) * 49152 + ((3 * mem + v) * 8 + (wg - 1) * 4 + warp) * 512 + lane * 16;
                    st_relaxed_v4(dst, pack_nz(acc[4 * j], acc[4 * j + 1]), pack_nz(acc[4 * j + 2], acc[4 * j + 3]),
                                  pack_nz(acc[4 * j + 4], acc[4 * j + 5]), pack_nz(acc[4 * j + 6], acc[4 * j + 7]));
                }
            if (tid == 128) TL(9);
        } else {
            mbar_wait(sb + OFF_BAR + (BAR_GO2 + 3) * 8, 0);
        }
        if ((tid & 127) == 0) mbar_expect_tx(sb + OFF_BAR + (BAR_XFULL + wg) * 8, 128 * 9 * 16);
        const char* qsrc = (const char*)g_qbuf + (size_t)((b * 4 + g) * 2 + r) * 49152 + (4 * wg + warp) * 4096 + lane * 16;
        {
            uint4 v[8];
            bool ok;
            do {
                probe_wait(qsrc - lane * 16 + (lane & 7) * 512);
                if (lane == 0 && warp == 0) TL(42 + wg);
                ok = true;
#pragma unroll
                for (int i = 0; i < 8; i++) v[i] = ld_relaxed_v4(qsrc + i * 512);
#pragma unroll
                for (int i = 0; i < 8; i++) ok = ok && valid4(v[i]);
            } while (!__all_sync(0xffffffffu, ok));
            const uint32_t a0 = qpiece + (16 * warp + (mi >> 1) * 8 + (lane & 7)) * 128;
#pragma unroll
            for (int i = 0; i < 8; i++)
                stsm_x4_t(a0 + (i >> 2) * 8192 + (((2 * (i & 3) + (mi & 1)) ^ (lane & 7)) << 4), v[i].x, v[i].y, v[i].z, v[i].w);
            fence_async_smem();
            if (lane == 0) mbar_arrive(sb + OFF_BAR + (BAR_GO2 + 2) * 8);
            named_sync(1 + wg);
        }
        asm volatile("barrier.cluster.wait.aligned;" ::: "memory");

        {
            const float c = 0.08838834764831845f * 1.4426950408889634f;
            float o[64];
            float m0 = 0.f, m1 = 0.f, l0 = 0.f, l1 = 0.f;
            if (lane == 0 && warp == 0) TL(10 + wg);
            const uint64_t dq = mkdesc(qpiece, 0, 1024);
#pragma unroll 1
            for (int j = 0; j < 8; j++) {
                float sc[64];
                const uint32_t kslot = (0x03142031u >> (4 * j)) & 7, vslot = (0x14203142u >> (4 * j)) & 7;
                TLC(j * 6 + 0);
                mbar_wait(sb + OFF_BAR + (BAR_FULL + kslot) * 8, (0x63u >> j) & 1);
                TLC(j * 6 + 1);
                {
                    const uint64_t dk = mkdesc(sb + OFF_RING + kslot * SLOT, 0, 1024);
                    wg_fence();
#pragma unroll
                    for (int kk = 0; kk < 8; kk++)
                        wgmma_n128_ss<0, 0>(sc, dq + (kk >> 2) * (8192 >> 4) + (kk & 3) * 2, dk + (kk >> 2) * (16384 >> 4) + (kk & 3) * 2, kk != 0);
                    wg_commit();
                    wg_wait<0>();
                    reg_fence(sc);
                }
                TLC(j * 6 + 2);
                if (lane == 0) mbar_arrive(sb + OFF_BAR + (BAR_EMPTY + kslot) * 8);
                if (j == 0) {
                    float x0 = fmaxf(sc[0], sc[1]), x1 = fmaxf(sc[2], sc[3]), y0 = fmaxf(sc[4], sc[5]), y1 = fmaxf(sc[6], sc[7]);
#pragma unroll
                    for (int i = 8; i < 64; i += 8) {
                        x0 = fmaxf(x0, fmaxf(sc[i], sc[i + 1])); x1 = fmaxf(x1, fmaxf(sc[i + 2], sc[i + 3]));
                        y0 = fmaxf(y0, fmaxf(sc[i + 4], sc[i + 5])); y1 = fmaxf(y1, fmaxf(sc[i + 6], sc[i + 7]));
                    }
                    x0 = fmaxf(x0, y0); x1 = fmaxf(x1, y1);
                    x0 = fmaxf(x0, __shfl_xor_sync(0xffffffffu, x0, 1)); x1 = fmaxf(x1, __shfl_xor_sync(0xffffffffu, x1, 1));
                    x0 = fmaxf(x0, __shfl_xor_sync(0xffffffffu, x0, 2)); x1 = fmaxf(x1, __shfl_xor_sync(0xffffffffu, x1, 2));
                    m0 = x0 * c; m1 = x1 * c;
                }
                if (j == 7 && lane == 0) mbar_arrive_remote(mapa(sb + OFF_BAR + (BAR_XFREE + wg) * 8, s ^ 1));
                uint32_t p[32];
                TLC(j * 6 + 3);
                mbar_wait(sb + OFF_BAR + (BAR_FULL + vslot) * 8, (0x73u >> j) & 1);
                TLC(j * 6 + 4);
                const uint64_t dv = mkdesc(sb + OFF_RING + vslot * SLOT, 16384, 1024);
#pragma unroll
                for (int ch = 0; ch < 2; ch++) {
#pragma unroll
                    for (int i = ch * 8; i < ch * 8 + 8; i++) {
                        const float e0 = ex2(fmaf(sc[4 * i], c, -m0)), e1 = ex2(fmaf(sc[4 * i + 1], c, -m0));
                        const float e2 = ex2(fmaf(sc[4 * i + 2], c, -m1)), e3 = ex2(fmaf(sc[4 * i + 3], c, -m1));
                        p[2 * i] = pack_bf16(e0, e1);
                        p[2 * i + 1] = pack_bf16(e2, e3);
                    }
                    wg_fence();
#pragma unroll
                    for (int kk = ch * 4; kk < ch * 4 + 4; kk++)
                        wgmma_n128_rs<1>(o, p[4 * kk], p[4 * kk + 1], p[4 * kk + 2], p[4 * kk + 3], dv + kk * (2048 >> 4), (j | kk) != 0);
                    wg_commit();
                    const uint32_t* q = p + ch * 16;
                    const uint32_t a = hadd2(hadd2(hadd2(q[0], q[2]), hadd2(q[4], q[6])), hadd2(hadd2(q[8], q[10]), hadd2(q[12], q[14])));
                    const uint32_t d = hadd2(hadd2(hadd2(q[1], q[3]), hadd2(q[5], q[7])), hadd2(hadd2(q[9], q[11]), hadd2(q[13], q[15])));
                    l0 += __uint_as_float(a << 16) + __uint_as_float(a & 0xffff0000u);
                    l1 += __uint_as_float(d << 16) + __uint_as_float(d & 0xffff0000u);
                }
                wg_wait<0>();
                reg_fence(o);
                if (lane == 0) mbar_arrive(sb + OFF_BAR + (BAR_EMPTY + vslot) * 8);
                TLC(j * 6 + 5);
            }

            if (__any_sync(0xffffffffu, !(l0 <= L_SAFE && l1 <= L_SAFE))) {
                float fo[64], fml[4];
                const size_t kvoff = (size_t)((b * 4 + g) * 2048 + s * 1024) * 256;
                const char* qs = (const char*)g_qbuf + (size_t)((b * 4 + g) * 2 + r) * 49152 + (4 * wg + warp) * 4096 + (threadIdx.x & 31) * 16;
                attention_fallback(fo, fml, qs, kc + kvoff, vc + kvoff, c);
#pragma unroll
                for (int i = 0; i < 64; i++) o[i] = fo[i];
                m0 = fml[0]; m1 = fml[1]; l0 = fml[2]; l1 = fml[3];
            }
            l0 += __shfl_xor_sync(0xffffffffu, l0, 1); l1 += __shfl_xor_sync(0xffffffffu, l1, 1);
            l0 += __shfl_xor_sync(0xffffffffu, l0, 2); l1 += __shfl_xor_sync(0xffffffffu, l1, 2);
            const int u = 4 * wg + warp;
            char* odst = (char*)g_obuf + (size_t)((g * 4 + t) * 16 + (4 * r + u / 3) * 2 + s) * 12288 + ((b & 1) * 3 + u % 3) * 2048 + lane * 16;
            if (s == 0) combine_and_store<0>(o, m0, m1, l0, l1, sb, wg, warp, lane, tid, odst);
            else combine_and_store<1>(o, m0, m1, l0, l1, sb, wg, warp, lane, tid, odst);
            if (lane == 0 && warp == 0) TL(13 + wg);
        }

        if (wg == 0) {
            const char* osrc = (const char*)g_obuf + (size_t)(g * 4 + t) * 196608 + warp * 3072 + lane * 16;
            uint4 va[12], vb[12];
            auto load = [&](uint4 (&v)[12], int n) {
#pragma unroll
                for (int y = 0; y < 12; y++) v[y] = ld_relaxed_v4(osrc + p3_kblock(2 * n + y / 6) * 12288 + (y % 6) * 512);
            };
            auto finish = [&](uint4 (&v)[12], int n) {
                while (true) {
                    bool ok = true;
#pragma unroll
                    for (int y = 0; y < 12; y++) ok = ok && valid4(v[y]);
                    if (__all_sync(0xffffffffu, ok)) break;
                    probe_wait(osrc - lane * 16 + p3_kblock(2 * n + ((lane >> 1) & 1)) * 12288 + (lane & 1) * 5 * 512);
                    load(v, n);
                }
#pragma unroll
                for (int h = 0; h < 2; h++) {
                    const int f = 32 + 2 * n + h, slot = f % NSLOT;
                    mbar_wait(sb + OFF_BAR + (BAR_EMPTY + slot) * 8, ((f / NSLOT) & 1) ^ 1);
#pragma unroll
                    for (int y = 0; y < 6; y++) {
                        const int z = warp * 6 + y;
                        const uint32_t a = sb + OFF_RING + slot * SLOT + 16384 + ((z >> 2) * 16 + (mi & 1) * 8 + (lane & 7)) * 128 +
                                           (((2 * (z & 3) + (mi >> 1)) ^ (lane & 7)) << 4);
                        stsm_x4(a, v[6 * h + y].x, v[6 * h + y].y, v[6 * h + y].z, v[6 * h + y].w);
                    }
                    fence_async_smem();
                    __syncwarp();
                    if (lane == 0) mbar_arrive(sb + OFF_BAR + (BAR_OFULL + slot) * 8);
                }
                if (n == 0 && tid == 0) TL(4);
                if (n == 7 && tid == 0) TL(5);
            };
            probe_wait(osrc - lane * 16 + p3_kblock((lane >> 1) & 1) * 12288 + (lane & 1) * 5 * 512);
            load(va, 0);
#pragma unroll
            for (int n = 0; n < 8; n += 2) {
                load(vb, n + 1);
                finish(va, n);
                if (n + 2 < 8) load(va, n + 2);
                finish(vb, n + 1);
            }
        } else {
            float acc[48];
            proj_mainloop<true>(acc, sb, wg - 1, lane);
            if (tid == 128) TL(40);
            named_sync(1 + wg);
            const uint32_t a0 = qpiece + ((mi >> 1) * 8 + (lane & 7)) * 128 + (((2 * warp + (mi & 1)) ^ (lane & 7)) << 4);
#pragma unroll
            for (int j = 0; j < 12; j += 2)
                stsm_x4_t(a0 + j * 1024, pack_bf16(acc[4 * j], acc[4 * j + 1]), pack_bf16(acc[4 * j + 2], acc[4 * j + 3]),
                          pack_bf16(acc[4 * j + 4], acc[4 * j + 5]), pack_bf16(acc[4 * j + 6], acc[4 * j + 7]));
            fence_async_smem();
            named_sync(1 + wg);
            if (warp == 0 && elect_one()) {
                tma_reduce_add_2d(&tm_out, col * 128 + (wg - 1) * 64, t * 96, qpiece);
                bulk_commit();
                bulk_wait0_read();
                if (wg == 1) TL(41);
            }
            __syncwarp();
        }
        TL_DUMP();
    }
}

typedef CUresult (*EncodeFn)(CUtensorMap*, CUtensorMapDataType, cuuint32_t, void*, const cuuint64_t*, const cuuint64_t*,
                             const cuuint32_t*, const cuuint32_t*, CUtensorMapInterleave, CUtensorMapSwizzle,
                             CUtensorMapL2promotion, CUtensorMapFloatOOBfill);

void make_map(EncodeFn enc, CUtensorMap* m, const void* ptr, int rank, uint64_t rows, uint64_t cols, uint32_t box_rows) {
    cuuint64_t dims[3] = {rank == 2 ? cols : 64, rows, cols / 64};
    cuuint64_t strides[2] = {cols * 2, 128};
    cuuint32_t box[3] = {64, box_rows, 2};
    cuuint32_t es[3] = {1, 1, 1};
    enc(m, CU_TENSOR_MAP_DATA_TYPE_BFLOAT16, rank, const_cast<void*>(ptr), dims, strides, box, es, CU_TENSOR_MAP_INTERLEAVE_NONE,
        CU_TENSOR_MAP_SWIZZLE_128B, CU_TENSOR_MAP_L2_PROMOTION_L2_256B, CU_TENSOR_MAP_FLOAT_OOB_FILL_NONE);
}

}

extern "C" void kernel_launch(void* const* d_in, const int* in_sizes, int n_in, void* d_out, int out_size) {
    (void)in_sizes; (void)n_in; (void)out_size;
    static EncodeFn enc = nullptr;
    if (!enc) {
        void* fn = nullptr;
        cudaDriverEntryPointQueryResult qr;
        cudaGetDriverEntryPoint("cuTensorMapEncodeTiled", &fn, cudaEnableDefault, &qr);
        enc = (EncodeFn)fn;
        cudaFuncSetAttribute(gqa_fused_kernel, cudaFuncAttributeMaxDynamicSharedMemorySize, SMEM_TOTAL);
    }
    CUtensorMap tx, twq, tk, tv, two, tout;
    make_map(enc, &tx, d_in[0], 2, 384, 1024, 96);
    make_map(enc, &tk, d_in[1], 3, 65536, 128, 128);
    make_map(enc, &tv, d_in[2], 2, 65536, 128, 128);
    make_map(enc, &twq, d_in[3], 3, 1024, 4096, 64);
    make_map(enc, &two, d_in[4], 3, 4096, 1024, 64);
    make_map(enc, &tout, d_out, 2, 384, 1024, 48);
    gqa_fused_kernel<<<NCTA + 4, NTHREADS, SMEM_TOTAL, cudaStreamPerThread>>>(tx, twq, tk, tv, two, tout, (__nv_bfloat16*)d_out,
        (const char*)d_in[3], (const char*)d_in[1], (const char*)d_in[2], (const char*)d_in[4]);
}
```

```cpp
#include <cuda_runtime.h>
#include <cuda_bf16.h>
#include <cuda.h>
#include <stdint.h>

namespace {

constexpr int NCTA = 128;
constexpr int NTHREADS = 512;
constexpr int SLOT = 32768;
constexpr int NSLOT = 5;
constexpr int OFF_ZERO = 0;
constexpr int OFF_Q = 8192;
constexpr int OFF_ML = OFF_Q + 49152;
constexpr int OFF_RING = OFF_ML + 6144;
constexpr int OFF_BAR = OFF_RING + NSLOT * SLOT;
constexpr int SMEM_BYTES = OFF_BAR + 704;
constexpr int NW3 = 9, NO3 = 6;
constexpr int NS1 = 7;
constexpr int BAR_FULL = 0, BAR_EMPTY = 5, BAR_XFREE = 10, BAR_QARR = 13, BAR_AOK = 14, BAR_P1DONE = 33, BAR_EMPTY3 = 15, BAR_ONES = 21,
              BAR_XFULL = 21, BAR_QFULL = 24, BAR_TMP = 27, BAR_TMP2 = 30, BAR_STAGEFREE = 34, BAR_GO2 = 35, BAR_EPOCH = 36,
              BAR_BOK = 37, BAR_GRP = 38, BAR_FULL3 = 41, BAR_OFULL = 47, BAR_WFULL = 53, BAR_END = 62, BAR_CDONE = 62, BAR_XML = 65,
              BAR_FULL1 = 68, BAR_EMPTY1 = 75;
constexpr int OFF_ZT = OFF_BAR + 82 * 8;

constexpr unsigned A_CNT = 16, B_CNT = 64;
constexpr uint32_t QPAR_BYTES = 64 * 49152;
#define PF_WO_START 20000
#define PF_WO_INTERVAL 1200
#define KV_EARLY 2
#define SCHED 3
#define PROBE_DELAY 650
#define H_KV_N 3
#define H_START 2000
#define H_KV_INT 0
#define H_WO_START 28000
#define H_WO_INT 500
#define ARR_CH 1
#define SKEW3 0
#define WSPACE 2
#define P1_SOLO 0
#define PRE 1
#define PRE_GAP 0
#define PRE_GAP0 0
#define QARR_LATE 1
#define WMASK (NW3 == 10 ? 0xAAA0u : 0x1FC0u)
#define P3MAP 0
#define GSYNC 0
#define WSTEP 2
#define H_SEQ 0x320
#define H_KV_INT0 500
#define OPTQ 1
#define H_W0 16
#define H_WSTART 1500
#define H_WINT 0
#define CLR_GAP 600
#define POLL_GAP 170
#define FASTQ 0
#define FASTO 0
#define ODELAY 0
#define QLATE 0
#define QD0 600
#define QD1 700
#define QD2 800
#define GATE 0
#define CLR_GAP2 400
#define PEEL 2
#define NCHK 2
#define CHB 0x850
#define KV_PFD 0
#define KV_PF0 2
#define MINIT 0
#define KV_GATE 4
#define K1_AT_END 0
#define EXP 0
#define BOTH_T 0
#define CADENCE 0
#define CAD0 1200
#define P3_SOLO 0
#define PF_KV_N 3
#define PF_KV_START 5000
#define PF_KV_INT 250
#define CLR_NS 300
#define GO2_AT 8
#define PLACE 1
constexpr int SPIN_LIMIT = 1 << 22;
constexpr float SCALE_LOG2E = 0.08838834764831845f * 1.4426950408889634f;
constexpr float L_SAFE = 1.0995116e12f;

__device__ uint4 g_qimg[2 * 64 * 49152 / 16];
__device__ uint4 g_oimg[16 * 16 * 12288 / 16];
__device__ unsigned g_aflag[8 * 32];
__device__ unsigned g_bflag[2 * 32];

__device__ __forceinline__ void TL(int) {}
__device__ __forceinline__ void TLP(int, uint32_t, int) {}
#define TLC(idx)
#define TLF(idx)
#define TLPF(c, sb, idx)
#define STALL_BEGIN()
#define STALL_END(idx)
#define TL_INIT()
#define TL_DUMP()
#define TL_DONE()
constexpr int SMEM_TOTAL = SMEM_BYTES;

__device__ __forceinline__ uint32_t smem_u32(const void* p) { return (uint32_t)__cvta_generic_to_shared(p); }
__device__ __forceinline__ void mbar_init(uint32_t bar, uint32_t cnt) {
    asm volatile("mbarrier.init.shared::cta.b64 [%0], %1;" ::"r"(bar), "r"(cnt) : "memory");
}
__device__ __forceinline__ void mbar_expect_tx(uint32_t bar, uint32_t bytes) {
    asm volatile("mbarrier.arrive.expect_tx.shared::cta.b64 _, [%0], %1;" ::"r"(bar), "r"(bytes) : "memory");
}
__device__ __forceinline__ void mbar_arrive(uint32_t bar) {
    asm volatile("mbarrier.arrive.shared::cta.b64 _, [%0];" ::"r"(bar) : "memory");
}
__device__ __forceinline__ void mbar_arrive_cnt(uint32_t bar, uint32_t cnt) {
    asm volatile("mbarrier.arrive.shared::cta.b64 _, [%0], %1;" ::"r"(bar), "r"(cnt) : "memory");
}
__device__ __forceinline__ void mbar_arrive_remote(uint32_t cluster_addr) {
    asm volatile("fence.release.sync_restrict::shared::cta.cluster;\n"
                 "mbarrier.arrive.relaxed.cluster.shared::cluster.b64 _, [%0];" ::"r"(cluster_addr) : "memory");
}
#define SPIN_GUARD(it) asm volatile("{\n.reg .pred q;\nsetp.gt.s32 q, %0, %1;\n@q trap;\n}" ::"r"(it), "n"(SPIN_LIMIT));
__device__ __forceinline__ void (mbar_wait)(uint32_t bar, uint32_t parity) {
    asm volatile(
        "{\n.reg .pred p, q;\n.reg .u32 c;\nmov.u32 c, 0;\n"
        "WAIT_LOOP:\n"
        "mbarrier.try_wait.parity.shared::cta.b64 p, [%0], %1;\n"
        "@p bra WAIT_DONE;\n"
        "add.u32 c, c, 1;\nsetp.gt.u32 q, c, %2;\n@q trap;\n"
        "bra WAIT_LOOP;\n"
        "WAIT_DONE:\n}\n" ::"r"(bar), "r"(parity), "n"(SPIN_LIMIT) : "memory");
}
__device__ __forceinline__ void (mbar_wait_cluster)(uint32_t bar, uint32_t parity) {
    asm volatile(
        "{\n.reg .pred p, q;\n.reg .u32 c;\nmov.u32 c, 0;\n"
        "WAIT_LOOP:\n"
        "mbarrier.try_wait.parity.acquire.cluster.shared::cta.b64 p, [%0], %1;\n"
        "@p bra WAIT_DONE;\n"
        "add.u32 c, c, 1;\nsetp.gt.u32 q, c, %2;\n@q trap;\n"
        "bra WAIT_LOOP;\n"
        "WAIT_DONE:\n}\n" ::"r"(bar), "r"(parity), "n"(SPIN_LIMIT) : "memory");
}
__device__ __forceinline__ bool elect_one() {
    uint32_t el;
    asm volatile("{\n.reg .pred p;\nelect.sync _|p, 0xffffffff;\nselp.u32 %0, 1, 0, p;\n}" : "=r"(el));
    return el != 0;
}
__device__ __forceinline__ void prefetch_tmap(const CUtensorMap* tm) { asm volatile("prefetch.tensormap [%0];" ::"l"(tm) : "memory"); }
__device__ __forceinline__ uint32_t mapa(uint32_t addr, uint32_t rank) {
    uint32_t r;
    asm("mapa.shared::cluster.u32 %0, %1, %2;" : "=r"(r) : "r"(addr), "r"(rank));
    return r;
}
__device__ __forceinline__ void tma_2d(uint32_t dst, const CUtensorMap* tm, int c0, int c1, uint32_t bar) {
    asm volatile("cp.async.bulk.tensor.2d.shared::cluster.global.mbarrier::complete_tx::bytes [%0], [%1, {%3, %4}], [%2];"
                 ::"r"(dst), "l"(tm), "r"(bar), "r"(c0), "r"(c1) : "memory");
}
__device__ __forceinline__ void tma_3d(uint32_t dst, const CUtensorMap* tm, int c0, int c1, int c2, uint32_t bar) {
    asm volatile("cp.async.bulk.tensor.3d.shared::cluster.global.mbarrier::complete_tx::bytes [%0], [%1, {%3, %4, %5}], [%2];"
                 ::"r"(dst), "l"(tm), "r"(bar), "r"(c0), "r"(c1), "r"(c2) : "memory");
}
__device__ __forceinline__ void bulk_g2s(uint32_t dst, const void* src, uint32_t bytes, uint32_t bar) {
    asm volatile("cp.async.bulk.shared::cluster.global.mbarrier::complete_tx::bytes [%0], [%1], %2, [%3];"
                 ::"r"(dst), "l"(src), "r"(bytes), "r"(bar) : "memory");
}
__device__ __forceinline__ void bulk_s2g(void* dst, uint32_t src, uint32_t bytes) {
    asm volatile("cp.async.bulk.global.shared::cta.bulk_group [%0], [%1], %2;" ::"l"(dst), "r"(src), "r"(bytes) : "memory");
}
__device__ __forceinline__ void tma_reduce_add_2d(const CUtensorMap* tm, int c0, int c1, uint32_t src) {
    asm volatile("cp.reduce.async.bulk.tensor.2d.global.shared::cta.add.tile.bulk_group [%0, {%2, %3}], [%1];"
                 ::"l"(tm), "r"(src), "r"(c0), "r"(c1) : "memory");
}
__device__ __forceinline__ void l2_prefetch(const void* src, uint32_t bytes) {
    asm volatile("cp.async.bulk.prefetch.L2.global [%0], %1;" ::"l"(src), "r"(bytes) : "memory");
}
__device__ __forceinline__ uint32_t clock32() {
    uint32_t c;
    asm volatile("mov.u32 %0, %%clock;" : "=r"(c)::"memory");
    return c;
}
__device__ __forceinline__ void bulk_commit() { asm volatile("cp.async.bulk.commit_group;" ::: "memory"); }
__device__ __forceinline__ void bulk_wait0() { asm volatile("cp.async.bulk.wait_group 0;" ::: "memory"); }
__device__ __forceinline__ void bulk_wait0_read() { asm volatile("cp.async.bulk.wait_group.read 0;" ::: "memory"); }
__device__ __forceinline__ void fence_async_smem() { asm volatile("fence.proxy.async.shared::cta;" ::: "memory"); }
__device__ __forceinline__ void fence_async_all() { asm volatile("fence.proxy.async;" ::: "memory"); }
__device__ __forceinline__ void red_release(unsigned* p, unsigned v) {
    asm volatile("red.release.gpu.global.add.u32 [%0], %1;" ::"l"(p), "r"(v) : "memory");
}
__device__ __forceinline__ unsigned ld_acquire(const unsigned* p) {
    unsigned v;
    asm volatile("ld.acquire.gpu.global.u32 %0, [%1];" : "=r"(v) : "l"(p) : "memory");
    return v;
}
__device__ __forceinline__ unsigned ld_relaxed(const unsigned* p) {
    unsigned v;
    asm volatile("ld.relaxed.gpu.global.u32 %0, [%1];" : "=r"(v) : "l"(p) : "memory");
    return v;
}
__device__ __forceinline__ void (flag_wait)(const unsigned* p, unsigned target) {
    asm volatile(
        "{\n.reg .pred p, q;\n.reg .u32 c, v;\nmov.u32 c, 0;\n"
        "FLAG_LOOP:\n"
        "ld.acquire.gpu.global.u32 v, [%0];\n"
        "sub.u32 v, v, %1;\nsetp.ge.s32 p, v, 0;\n"
        "@p bra FLAG_DONE;\n"
        "add.u32 c, c, 1;\nsetp.gt.u32 q, c, %2;\n@q trap;\n"
        "bra FLAG_LOOP;\n"
        "FLAG_DONE:\n}\n" ::"l"(p), "r"(target), "n"(SPIN_LIMIT) : "memory");
}
__device__ __forceinline__ void named_sync(int id) { asm volatile("bar.sync %0, 128;" ::"r"(id) : "memory"); }
__device__ __forceinline__ void wg_fence() { asm volatile("wgmma.fence.sync.aligned;" ::: "memory"); }
__device__ __forceinline__ void wg_commit() { asm volatile("wgmma.commit_group.sync.aligned;" ::: "memory"); }
template <int N> __device__ __forceinline__ void wg_wait() { asm volatile("wgmma.wait_group.sync.aligned %0;" ::"n"(N) : "memory"); }
template <int N> __device__ __forceinline__ void reg_fence(float (&d)[N]) {
#pragma unroll
    for (int i = 0; i < N; i++) asm volatile("" : "+f"(d[i])::"memory");
}
__device__ __forceinline__ uint64_t mkdesc(uint32_t addr, uint32_t lbo, uint32_t sbo) {
    return (uint64_t)((addr & 0x3FFFF) >> 4) | ((uint64_t)(lbo >> 4) << 16) | ((uint64_t)(sbo >> 4) << 32) | (1ull << 62);
}
__device__ __forceinline__ uint32_t pack_bf16(float lo, float hi) {
    uint32_t r;
    asm("cvt.rn.bf16x2.f32 %0, %1, %2;" : "=r"(r) : "f"(hi), "f"(lo));
    return r;
}
__device__ __forceinline__ uint32_t hadd2(uint32_t a, uint32_t b) {
    uint32_t r;
    asm("add.rn.bf16x2 %0, %1, %2;" : "=r"(r) : "r"(a), "r"(b));
    return r;
}
__device__ __forceinline__ float ex2(float x) {
    float y;
    asm("ex2.approx.ftz.f32 %0, %1;" : "=f"(y) : "f"(x));
    return y;
}
__device__ __forceinline__ void stsm_x4(uint32_t addr, uint32_t r0, uint32_t r1, uint32_t r2, uint32_t r3) {
    asm volatile("stmatrix.sync.aligned.m8n8.x4.shared.b16 [%0], {%1, %2, %3, %4};" ::"r"(addr), "r"(r0), "r"(r1), "r"(r2), "r"(r3) : "memory");
}
__device__ __forceinline__ void stsm_x4_t(uint32_t addr, uint32_t r0, uint32_t r1, uint32_t r2, uint32_t r3) {
    asm volatile("stmatrix.sync.aligned.m8n8.x4.trans.shared.b16 [%0], {%1, %2, %3, %4};" ::"r"(addr), "r"(r0), "r"(r1), "r"(r2), "r"(r3) : "memory");
}
__device__ __forceinline__ void st_async_v4(uint32_t addr, float a, float b, float c, float d, uint32_t bar) {
    asm volatile("st.async.weak.shared::cluster.mbarrier::complete_tx::bytes.v4.f32 [%0], {%1, %2, %3, %4}, [%5];"
                 ::"r"(addr), "f"(a), "f"(b), "f"(c), "f"(d), "r"(bar) : "memory");
}
__device__ __forceinline__ void st_async_v4u(uint32_t addr, uint32_t a, uint32_t b, uint32_t c, uint32_t d, uint32_t bar) {
    asm volatile("st.async.weak.shared::cluster.mbarrier::complete_tx::bytes.v4.b32 [%0], {%1, %2, %3, %4}, [%5];"
                 ::"r"(addr), "r"(a), "r"(b), "r"(c), "r"(d), "r"(bar) : "memory");
}
__device__ __forceinline__ uint32_t lds_u32(uint32_t addr) {
    uint32_t v;
    asm volatile("ld.shared.u32 %0, [%1];" : "=r"(v) : "r"(addr) : "memory");
    return v;
}
__device__ __forceinline__ float rcp_fast(float x) {
    float y;
    asm("rcp.approx.ftz.f32 %0, %1;" : "=f"(y) : "f"(x));
    return y;
}
__device__ __forceinline__ float bf_lo(uint32_t w) { return __uint_as_float(w << 16); }
__device__ __forceinline__ float bf_hi(uint32_t w) { return __uint_as_float(w & 0xffff0000u); }
__device__ __forceinline__ float4 lds_v4(uint32_t addr) {
    float4 v;
    asm volatile("ld.shared.v4.f32 {%0, %1, %2, %3}, [%4];" : "=f"(v.x), "=f"(v.y), "=f"(v.z), "=f"(v.w) : "r"(addr) : "memory");
    return v;
}

__device__ __forceinline__ uint4 ld_relaxed_v4(const void* p) {
    uint4 v;
    asm volatile("ld.relaxed.gpu.global.v4.u32 {%0, %1, %2, %3}, [%4];" : "=r"(v.x), "=r"(v.y), "=r"(v.z), "=r"(v.w) : "l"(p) : "memory");
    return v;
}
__device__ __forceinline__ void st_relaxed_v4(void* p, uint32_t a, uint32_t b, uint32_t c, uint32_t d) {
    asm volatile("st.relaxed.gpu.global.v4.u32 [%0], {%1, %2, %3, %4};" ::"l"(p), "r"(a), "r"(b), "r"(c), "r"(d) : "memory");
}
__device__ __forceinline__ uint32_t pack_nz(float lo, float hi) {
    const uint32_t w = pack_bf16(lo, hi);
    return w == 0u ? 0x80008000u : w;
}
__device__ __forceinline__ bool valid4(const uint4& v) { return min(min(v.x, v.y), min(v.z, v.w)) != 0u; }
__device__ __forceinline__ void (probe_wait)(const void* p) {
    asm volatile(
        "{\n.reg .pred p, q;\n.reg .u32 c, v;\nmov.u32 c, 0;\n"
        "PROBE_LOOP:\n"
        "ld.relaxed.gpu.global.u32 v, [%0];\n"
        "setp.ne.u32 p, v, 0;\n"
        "vote.sync.all.pred p, p, 0xffffffff;\n"
        "@p bra PROBE_DONE;\n"
        "add.u32 c, c, 1;\nsetp.gt.u32 q, c, %1;\n@q trap;\n"
        "bra PROBE_LOOP;\n"
        "PROBE_DONE:\n}\n" ::"l"(p), "n"(SPIN_LIMIT) : "memory");
}
__device__ __forceinline__ void probe_wait_fast(const void* p) {
    unsigned v[3];
#pragma unroll
    for (int i = 0; i < 3; i++) {
        v[i] = ld_relaxed((const unsigned*)p);
        if (i < 2) { const uint32_t t = clock32(); while ((int)(clock32() - t) < POLL_GAP) ; }
    }
#pragma unroll 1
    for (int it = 0;; it++) {
        if (__all_sync(0xffffffffu, v[0] != 0u)) break;
        v[0] = ld_relaxed((const unsigned*)p);
        if (__all_sync(0xffffffffu, v[1] != 0u)) break;
        v[1] = ld_relaxed((const unsigned*)p);
        if (__all_sync(0xffffffffu, v[2] != 0u)) break;
        v[2] = ld_relaxed((const unsigned*)p);
        asm volatile("{\n.reg .pred q;\nsetp.gt.s32 q, %0, %1;\n@q trap;\n}" ::"r"(it), "n"(SPIN_LIMIT));
    }
}
__device__ __forceinline__ void bar_sync_n(int id, int n) { asm volatile("bar.sync %0, %1;" ::"r"(id), "r"(n) : "memory"); }
__device__ __forceinline__ void bar_arrive_n(int id, int n) { asm volatile("bar.arrive %0, %1;" ::"r"(id), "r"(n) : "memory"); }
__device__ __forceinline__ uint32_t movm_t(uint32_t a) {
    uint32_t d;
    asm volatile("movmatrix.sync.aligned.m8n8.trans.b16 %0, %1;" : "=r"(d) : "r"(a));
    return d;
}
__device__ __forceinline__ void mma_16816(float* d, uint32_t a0, uint32_t a1, uint32_t a2, uint32_t a3, uint32_t b0, uint32_t b1) {
    asm volatile("mma.sync.aligned.m16n8k16.row.col.f32.bf16.bf16.f32 {%0, %1, %2, %3}, {%4, %5, %6, %7}, {%8, %9}, {%0, %1, %2, %3};"
                 : "+f"(d[0]), "+f"(d[1]), "+f"(d[2]), "+f"(d[3]) : "r"(a0), "r"(a1), "r"(a2), "r"(a3), "r"(b0), "r"(b1));
}

template <int V> struct Int { static constexpr int value = V; };

template <int TA, int TB>
__device__ __forceinline__ void wgmma_n96_ss(float (&d)[48], uint64_t da, uint64_t db, int scale_d) {
    asm volatile("{\n.reg .pred p;\nsetp.ne.b32 p, %50, 0;\n"
        "wgmma.mma_async.sync.aligned.m64n96k16.f32.bf16.bf16 {"
        "%0, %1, %2, %3, %4, %5, %6, %7, %8, %9, %10, %11, %12, %13, %14, %15, "
        "%16, %17, %18, %19, %20, %21, %22, %23, %24, %25, %26, %27, %28, %29, %30, %31, "
        "%32, %33, %34, %35, %36, %37, %38, %39, %40, %41, %42, %43, %44, %45, %46, %47}, "
        "%48, %49, p, 1, 1, %51, %52;\n}\n"
        : "+f"(d[0]), "+f"(d[1]), "+f"(d[2]), "+f"(d[3]), "+f"(d[4]), "+f"(d[5]), "+f"(d[6]), "+f"(d[7]),
          "+f"(d[8]), "+f"(d[9]), "+f"(d[10]), "+f"(d[11]), "+f"(d[12]), "+f"(d[13]), "+f"(d[14]), "+f"(d[15]),
          "+f"(d[16]), "+f"(d[17]), "+f"(d[18]), "+f"(d[19]), "+f"(d[20]), "+f"(d[21]), "+f"(d[22]), "+f"(d[23]),
          "+f"(d[24]), "+f"(d[25]), "+f"(d[26]), "+f"(d[27]), "+f"(d[28]), "+f"(d[29]), "+f"(d[30]), "+f"(d[31]),
          "+f"(d[32]), "+f"(d[33]), "+f"(d[34]), "+f"(d[35]), "+f"(d[36]), "+f"(d[37]), "+f"(d[38]), "+f"(d[39]),
          "+f"(d[40]), "+f"(d[41]), "+f"(d[42]), "+f"(d[43]), "+f"(d[44]), "+f"(d[45]), "+f"(d[46]), "+f"(d[47])
        : "l"(da), "l"(db), "r"(scale_d), "n"(TA), "n"(TB));
}
template <int TA, int TB>
__device__ __forceinline__ void wgmma_n128_ss(float (&d)[64], uint64_t da, uint64_t db, int scale_d) {
    asm volatile("{\n.reg .pred p;\nsetp.ne.b32 p, %66, 0;\n"
        "wgmma.mma_async.sync.aligned.m64n128k16.f32.bf16.bf16 {"
        "%0, %1, %2, %3, %4, %5, %6, %7, %8, %9, %10, %11, %12, %13, %14, %15, "
        "%16, %17, %18, %19, %20, %21, %22, %23, %24, %25, %26, %27, %28, %29, %30, %31, "
        "%32, %33, %34, %35, %36, %37, %38, %39, %40, %41, %42, %43, %44, %45, %46, %47, "
        "%48, %49, %50, %51, %52, %53, %54, %55, %56, %57, %58, %59, %60, %61, %62, %63}, "
        "%64, %65, p, 1, 1, %67, %68;\n}\n"
        : "+f"(d[0]), "+f"(d[1]), "+f"(d[2]), "+f"(d[3]), "+f"(d[4]), "+f"(d[5]), "+f"(d[6]), "+f"(d[7]),
          "+f"(d[8]), "+f"(d[9]), "+f"(d[10]), "+f"(d[11]), "+f"(d[12]), "+f"(d[13]), "+f"(d[14]), "+f"(d[15]),
          "+f"(d[16]), "+f"(d[17]), "+f"(d[18]), "+f"(d[19]), "+f"(d[20]), "+f"(d[21]), "+f"(d[22]), "+f"(d[23]),
          "+f"(d[24]), "+f"(d[25]), "+f"(d[26]), "+f"(d[27]), "+f"(d[28]), "+f"(d[29]), "+f"(d[30]), "+f"(d[31]),
          "+f"(d[32]), "+f"(d[33]), "+f"(d[34]), "+f"(d[35]), "+f"(d[36]), "+f"(d[37]), "+f"(d[38]), "+f"(d[39]),
          "+f"(d[40]), "+f"(d[41]), "+f"(d[42]), "+f"(d[43]), "+f"(d[44]), "+f"(d[45]), "+f"(d[46]), "+f"(d[47]),
          "+f"(d[48]), "+f"(d[49]), "+f"(d[50]), "+f"(d[51]), "+f"(d[52]), "+f"(d[53]), "+f"(d[54]), "+f"(d[55]),
          "+f"(d[56]), "+f"(d[57]), "+f"(d[58]), "+f"(d[59]), "+f"(d[60]), "+f"(d[61]), "+f"(d[62]), "+f"(d[63])
        : "l"(da), "l"(db), "r"(scale_d), "n"(TA), "n"(TB));
}
template <int TB>
__device__ __forceinline__ void wgmma_n128_rs(float (&d)[64], uint32_t a0, uint32_t a1, uint32_t a2, uint32_t a3, uint64_t db, int scale_d) {
    asm volatile("{\n.reg .pred p;\nsetp.ne.b32 p, %69, 0;\n"
        "wgmma.mma_async.sync.aligned.m64n128k16.f32.bf16.bf16 {"
        "%0, %1, %2, %3, %4, %5, %6, %7, %8, %9, %10, %11, %12, %13, %14, %15, "
        "%16, %17, %18, %19, %20, %21, %22, %23, %24, %25, %26, %27, %28, %29, %30, %31, "
        "%32, %33, %34, %35, %36, %37, %38, %39, %40, %41, %42, %43, %44, %45, %46, %47, "
        "%48, %49, %50, %51, %52, %53, %54, %55, %56, %57, %58, %59, %60, %61, %62, %63}, "
        "{%64, %65, %66, %67}, %68, p, 1, 1, %70;\n}\n"
        : "+f"(d[0]), "+f"(d[1]), "+f"(d[2]), "+f"(d[3]), "+f"(d[4]), "+f"(d[5]), "+f"(d[6]), "+f"(d[7]),
          "+f"(d[8]), "+f"(d[9]), "+f"(d[10]), "+f"(d[11]), "+f"(d[12]), "+f"(d[13]), "+f"(d[14]), "+f"(d[15]),
          "+f"(d[16]), "+f"(d[17]), "+f"(d[18]), "+f"(d[19]), "+f"(d[20]), "+f"(d[21]), "+f"(d[22]), "+f"(d[23]),
          "+f"(d[24]), "+f"(d[25]), "+f"(d[26]), "+f"(d[27]), "+f"(d[28]), "+f"(d[29]), "+f"(d[30]), "+f"(d[31]),
          "+f"(d[32]), "+f"(d[33]), "+f"(d[34]), "+f"(d[35]), "+f"(d[36]), "+f"(d[37]), "+f"(d[38]), "+f"(d[39]),
          "+f"(d[40]), "+f"(d[41]), "+f"(d[42]), "+f"(d[43]), "+f"(d[44]), "+f"(d[45]), "+f"(d[46]), "+f"(d[47]),
          "+f"(d[48]), "+f"(d[49]), "+f"(d[50]), "+f"(d[51]), "+f"(d[52]), "+f"(d[53]), "+f"(d[54]), "+f"(d[55]),
          "+f"(d[56]), "+f"(d[57]), "+f"(d[58]), "+f"(d[59]), "+f"(d[60]), "+f"(d[61]), "+f"(d[62]), "+f"(d[63])
        : "r"(a0), "r"(a1), "r"(a2), "r"(a3), "l"(db), "r"(scale_d), "n"(TB));
}

template <bool P3>
__device__ __forceinline__ void proj_mainloop(float (&acc)[48], uint32_t sb, int half, int lane) {
    constexpr int F0 = P3 ? 32 : 0;
    int slot = F0 % NSLOT, par = (F0 / NSLOT) & 1, opar = 0;
    int prev = 0;
#pragma unroll 1
    for (int kb = 0; kb < 16; kb++) {
        mbar_wait(sb + OFF_BAR + (BAR_FULL + slot) * 8, par);
        if (P3) mbar_wait(sb + OFF_BAR + (BAR_OFULL + slot) * 8, opar);
        const uint32_t st = __shfl_sync(0xffffffffu, sb + OFF_RING + slot * SLOT, 0);
        const uint64_t da = mkdesc(st + half * 8192, 0, 1024);
        const uint64_t db = mkdesc(st + 16384, 0, 1024);
        wg_fence();
#pragma unroll
        for (int kk = 0; kk < 4; kk++) wgmma_n96_ss<1, 0>(acc, da + kk * (2048 >> 4), db + kk * (32 >> 4), (kb | kk) != 0);
        wg_commit();
        if (threadIdx.x == 128 && (kb & 1) == 0) TL((P3 ? 56 : 48) + kb / 2);
        if (kb > 0) {
            wg_wait<1>();
            if (lane == 0) mbar_arrive_cnt(sb + OFF_BAR + (BAR_EMPTY + prev) * 8, 2 - half);
        }
        prev = slot;
        if (++slot == NSLOT) { slot = 0; par ^= 1; }
        if (slot == F0 % NSLOT) opar ^= 1;
    }
    wg_wait<0>();
    reg_fence(acc);
    if (lane == 0) mbar_arrive_cnt(sb + OFF_BAR + (BAR_EMPTY + prev) * 8, 2 - half);
}

__device__ __noinline__ void attention_fallback(float* o, float* ml, const char* qsrc, const char* kptr, const char* vptr, float c) {
    const int lane = threadIdx.x & 31;
    uint32_t q[32];
#pragma unroll
    for (int i = 0; i < 8; i++) {
        const uint4 v = ld_relaxed_v4(qsrc + i * 512);
        q[4 * i] = movm_t(v.x); q[4 * i + 2] = movm_t(v.y); q[4 * i + 1] = movm_t(v.z); q[4 * i + 3] = movm_t(v.w);
    }
    float acc[64];
#pragma unroll
    for (int i = 0; i < 64; i++) acc[i] = 0.f;
    float m0 = -INFINITY, m1 = -INFINITY, l0 = 0.f, l1 = 0.f;
#pragma unroll 1
    for (int k0 = 0; k0 < 1024; k0 += 16) {
        float sc[8];
#pragma unroll
        for (int i = 0; i < 8; i++) sc[i] = 0.f;
#pragma unroll
        for (int nb = 0; nb < 2; nb++)
#pragma unroll
            for (int kk = 0; kk < 8; kk++) {
                const char* kp = kptr + (size_t)(k0 + nb * 8 + (lane >> 2)) * 256 + kk * 32 + (lane & 3) * 4;
                mma_16816(sc + 4 * nb, q[4 * kk], q[4 * kk + 1], q[4 * kk + 2], q[4 * kk + 3], *(const uint32_t*)kp, *(const uint32_t*)(kp + 16));
            }
        float n0 = fmaxf(fmaxf(sc[0], sc[1]), fmaxf(sc[4], sc[5])) * c, n1 = fmaxf(fmaxf(sc[2], sc[3]), fmaxf(sc[6], sc[7])) * c;
        n0 = fmaxf(n0, __shfl_xor_sync(0xffffffffu, n0, 1)); n1 = fmaxf(n1, __shfl_xor_sync(0xffffffffu, n1, 1));
        n0 = fmaxf(n0, __shfl_xor_sync(0xffffffffu, n0, 2)); n1 = fmaxf(n1, __shfl_xor_sync(0xffffffffu, n1, 2));
        n0 = fmaxf(n0, m0); n1 = fmaxf(n1, m1);
        const float al0 = ex2(m0 - n0), al1 = ex2(m1 - n1);
        m0 = n0; m1 = n1;
        float e[8];
#pragma unroll
        for (int i = 0; i < 8; i++) e[i] = ex2(fmaf(sc[i], c, (i & 2) ? -n1 : -n0));
        l0 = l0 * al0 + (e[0] + e[1]) + (e[4] + e[5]);
        l1 = l1 * al1 + (e[2] + e[3]) + (e[6] + e[7]);
        const uint32_t p0 = pack_bf16(e[0], e[1]), p1 = pack_bf16(e[2], e[3]), p2 = pack_bf16(e[4], e[5]), p3 = pack_bf16(e[6], e[7]);
#pragma unroll
        for (int nb = 0; nb < 16; nb++) {
            const unsigned short* vp = (const unsigned short*)(vptr + (size_t)(k0 + (lane & 3) * 2) * 256) + nb * 8 + (lane >> 2);
            const uint32_t b0 = vp[0] | ((uint32_t)vp[128] << 16), b1 = vp[8 * 128] | ((uint32_t)vp[9 * 128] << 16);
            acc[4 * nb] *= al0; acc[4 * nb + 1] *= al0; acc[4 * nb + 2] *= al1; acc[4 * nb + 3] *= al1;
            mma_16816(acc + 4 * nb, p0, p1, p2, p3, b0, b1);
        }
    }
#pragma unroll
    for (int i = 0; i < 64; i++) o[i] = acc[i];
    ml[0] = m0; ml[1] = m1; ml[2] = l0; ml[3] = l1;
}

template <int S>
__device__ __forceinline__ void combine_and_store(float (&o)[64], float m0, float m1, float l0, float l1, uint32_t sb,
                                                  int wg, int warp, int lane, int tid, char* odst) {
    constexpr int KEEP = S * 32, SEND = 32 - KEEP;
    const uint32_t wbuf = sb + OFF_Q + wg * 16384 + warp * 4096;
    const uint32_t peer_buf = mapa(wbuf + lane * 16, S ^ 1);
    const uint32_t peer_ml = mapa(sb + OFF_ML + tid * 16, S ^ 1);
    const uint32_t peer_bar = mapa(sb + OFF_BAR + (BAR_XFULL + wg) * 8, S ^ 1);
    mbar_wait_cluster(sb + OFF_BAR + (BAR_XFREE + wg) * 8, 0);
    st_async_v4(peer_ml, m0, m1, l0, l1, peer_bar);
#pragma unroll
    for (int i = 0; i < 8; i++)
        st_async_v4(peer_buf + i * 512, o[SEND + 4 * i], o[SEND + 4 * i + 1], o[SEND + 4 * i + 2], o[SEND + 4 * i + 3], peer_bar);
    mbar_wait_cluster(sb + OFF_BAR + (BAR_XFULL + wg) * 8, 0);
    const float4 pml = lds_v4(sb + OFF_ML + tid * 16);
    const float mm0 = fmaxf(m0, pml.x), mm1 = fmaxf(m1, pml.y);
    float a0 = ex2(m0 - mm0), b0 = ex2(pml.x - mm0);
    float a1 = ex2(m1 - mm1), b1 = ex2(pml.y - mm1);
    const float inv0 = 1.0f / (a0 * l0 + b0 * pml.z), inv1 = 1.0f / (a1 * l1 + b1 * pml.w);
    a0 *= inv0; b0 *= inv0; a1 *= inv1; b1 *= inv1;
#pragma unroll
    for (int q = 0; q < 4; q++) {
        const float4 v = lds_v4(wbuf + lane * 16 + (2 * q) * 512), w = lds_v4(wbuf + lane * 16 + (2 * q + 1) * 512);
        const int i = KEEP + 8 * q;
        st_relaxed_v4(odst + q * 512, pack_nz(o[i] * a0 + v.x * b0, o[i + 1] * a0 + v.y * b0), pack_nz(o[i + 2] * a1 + v.z * b1, o[i + 3] * a1 + v.w * b1),
                      pack_nz(o[i + 4] * a0 + w.x * b0, o[i + 5] * a0 + w.y * b0), pack_nz(o[i + 6] * a1 + w.z * b1, o[i + 7] * a1 + w.w * b1));
    }
}

__device__ __forceinline__ int p3_kblock(int n) { return (n >> 2) * 2 + (n & 1) + ((n >> 1) & 1) * 8; }

__global__ void __cluster_dims__(2, 1, 1) __launch_bounds__(NTHREADS, 1)
gqa_fused_kernel(const __grid_constant__ CUtensorMap tm_x, const __grid_constant__ CUtensorMap tm_wq,
                 const __grid_constant__ CUtensorMap tm_k, const __grid_constant__ CUtensorMap tm_v,
                 const __grid_constant__ CUtensorMap tm_wo, const __grid_constant__ CUtensorMap tm_out,
                 __nv_bfloat16* __restrict__ out, const char* __restrict__ wq, const char* __restrict__ kc,
                 const char* __restrict__ vc, const char* __restrict__ wo) {
    extern __shared__ __align__(1024) unsigned char smem[];
    uint32_t sb = smem_u32(smem);
    asm volatile("mov.u32 %0, %0;" : "+r"(sb));
    const int tid = threadIdx.x, lane = tid & 31;
    const int wg = __shfl_sync(0xffffffffu, tid >> 7, 0), warp = __shfl_sync(0xffffffffu, (tid >> 5) & 3, 0);
    const int bid = blockIdx.x;
    const int mem = bid & 3, r = (bid >> 2) & 1, t = (bid >> 3) & 3, g = bid >> 5;
    const int s = mem & 1, b = 2 * t + (mem >> 1), col = bid & 7;
    const int head = g * 8 + r * 4 + mem;

    TL_INIT();
    if (wg == 3 && warp == 0) {
        if (elect_one()) {
            TL(0);
#pragma unroll
            for (int i = 0; i < NSLOT; i++) {
                mbar_init(sb + OFF_BAR + (BAR_FULL + i) * 8, 1);
                mbar_init(sb + OFF_BAR + (BAR_EMPTY + i) * 8, 12);
                mbar_init(sb + OFF_BAR + (BAR_OFULL + i) * 8, 4);
            }
#pragma unroll
            for (int i = 0; i < 3; i++) {
                mbar_init(sb + OFF_BAR + (BAR_XFREE + i) * 8, 4);
                mbar_init(sb + OFF_BAR + (BAR_XFULL + i) * 8, 1);
            }
            mbar_init(sb + OFF_BAR + BAR_GO2 * 8, 1);
            mbar_init(sb + OFF_BAR + (BAR_GO2 + 1) * 8, 1);
            mbar_init(sb + OFF_BAR + (BAR_GO2 + 2) * 8, 12);
            mbar_init(sb + OFF_BAR + (BAR_GO2 + 3) * 8, 1);
            asm volatile("fence.mbarrier_init.release.cluster;" ::: "memory");
            fence_async_smem();
#pragma unroll
            for (int f = 0; f < NSLOT; f++) {
                const uint32_t full = sb + OFF_BAR + (BAR_FULL + f) * 8, st = sb + OFF_RING + f * SLOT;
                mbar_expect_tx(full, 28672);
                tma_3d(st, &tm_wq, 0, f * 64, head * 2, full);
                tma_2d(st + 16384, &tm_x, f * 64, t * 96, full);
            }
#pragma unroll
            for (int f = NSLOT; f < NSLOT + PF_DIST; f++) l2_prefetch(wq + (size_t)f * 524288 + bid * 4096, 4096);
            TL(1);
        }
    } else if (wg == 3 && warp == 1) {
        if (elect_one()) { prefetch_tmap(&tm_k); prefetch_tmap(&tm_v); prefetch_tmap(&tm_wo); prefetch_tmap(&tm_out); }
    }
    __syncthreads();
    asm volatile("barrier.cluster.arrive.relaxed.aligned;" ::: "memory");

    if (wg == 3) {
        asm volatile("setmaxnreg.dec.sync.aligned.u32 32;");
        if (warp == 0) {
            if (elect_one()) {
                uint32_t bar = sb + OFF_BAR, st = sb + OFF_RING;
                uint32_t par = 0;
                auto advance = [&]() {
                    bar += 8; st += SLOT;
                    if (bar == sb + OFF_BAR + NSLOT * 8) { bar = sb + OFF_BAR; st = sb + OFF_RING; par ^= 1; }
                };
#pragma unroll 1
                for (int f = NSLOT; f < 16; f++) {
                    if (f == 15) {
                        mbar_wait(sb + OFF_BAR + (BAR_GO2 + 1) * 8, 0);
                        unsigned at;
                        asm volatile("ld.shared.u32 %0, [%1];" : "=r"(at) : "r"(sb + OFF_ZT) : "memory");
                        flag_wait(g_aflag + (bid >> 2) * 32, at);
                        mbar_arrive(sb + OFF_BAR + (BAR_GO2 + 3) * 8);
                    }
                    mbar_wait(bar + BAR_EMPTY * 8, par);
                    mbar_expect_tx(bar, 28672);
                    tma_3d(st, &tm_wq, 0, f * 64, head * 2, bar);
                    tma_2d(st + 16384, &tm_x, f * 64, t * 96, bar);
                    if (f + PF_DIST < 16) l2_prefetch(wq + (size_t)(f + PF_DIST) * 524288 + bid * 4096, 4096);
                    advance();
                }
                const int kvrow = (b * 4 + g) * 2048 + s * 1024;
                TL(2);
#pragma unroll 1
                for (int f = 0; f < 16; f++) {
                    if (f == KV_EARLY) { mbar_wait(sb + OFF_BAR + (BAR_GO2 + 2) * 8, 0); TL(3); }
                    if (f == 8) mbar_arrive(sb + OFF_BAR + BAR_GO2 * 8);
                    if (f == 15) {
                        mbar_wait(sb + OFF_BAR + (BAR_GO2 + 1) * 8, 1);
                        unsigned bt;
                        asm volatile("ld.shared.u32 %0, [%1];" : "=r"(bt) : "r"(sb + OFF_ZT + 4) : "memory");
                        flag_wait(g_bflag + t * 32, bt);
                        fence_async_all();
                    }
                    mbar_wait(bar + BAR_EMPTY * 8, par);
                    mbar_expect_tx(bar, 32768);
                    tma_3d(st, (f & 1) ? &tm_v : &tm_k, 0, kvrow + (f >> 1) * 128, 0, bar);
                    TL(16 + f);
                    advance();
                }
#pragma unroll 1
                for (int f = 0; f < 16; f++) {
                    mbar_wait(bar + BAR_EMPTY * 8, par);
                    mbar_expect_tx(bar, 16384);
                    tma_3d(st, &tm_wo, 0, g * 1024 + p3_kblock(f) * 64, col * 2, bar);
                    advance();
                }
                TL(6);
            }
        } else if (warp == 1) {
            if (elect_one()) {
                uint32_t next = clock32() + PF_WO_START;
                mbar_wait(sb + OFF_BAR + (BAR_GO2 + 3) * 8, 0);
                {
                    uint32_t nx = clock32() + PF_KV_DELAY;
                    const size_t kvoff = ((size_t)((b * 4 + g) * 2048 + s * 1024 + r * 64)) * 256;
#pragma unroll 1
                    for (int c = KV_EARLY * (16384 / PF_CH); c < PF_KV_END * (16384 / PF_CH); c++) {
                        const int f = c / (16384 / PF_CH);
                        while ((int)(clock32() - nx) < 0) __nanosleep(40);
                        l2_prefetch(((f & 1) ? vc : kc) + kvoff + (size_t)(f >> 1) * 32768 + (c % (16384 / PF_CH)) * PF_CH, PF_CH);
                        nx += PF_KV_INT;
                    }
                }
#pragma unroll 1
                for (int i = 0; i < 16; i++) {
                    while ((int)(clock32() - next) < 0) __nanosleep(200);
                    l2_prefetch(wo + (size_t)g * 2097152 + (size_t)p3_kblock(i) * 131072 + (bid & 31) * 4096, 4096);
                    next += PF_WO_INTERVAL;
                }
                TL(7);
            }
        } else {
            const int i6 = tid & 63;
            unsigned* aflag = g_aflag + (bid >> 2) * 32;
            unsigned* bflag = g_bflag + t * 32;
            if (i6 == 0) {
                const unsigned av = ld_relaxed(aflag), bv = ld_relaxed(bflag);
                asm volatile("st.shared.v2.u32 [%0], {%1, %2};" ::"r"(sb + OFF_ZT), "r"((av / A_CNT + 1) * A_CNT), "r"((bv / B_CNT + 1) * B_CNT) : "memory");
            }
            uint4* qz = g_qbuf + (size_t)((b * 4 + g) * 2 + r) * 3072 + s * 1536 + i6;
#pragma unroll 1
            for (int k = 0; k < 24; k++) { qz[k * 64] = make_uint4(0, 0, 0, 0); if (CLR_SLEEP) __nanosleep(CLR_SLEEP); }
            bar_sync_n(4, 64);
            if (i6 == 0) { red_release(aflag, 1); mbar_arrive(sb + OFF_BAR + (BAR_GO2 + 1) * 8); }
            mbar_wait(sb + OFF_BAR + BAR_GO2 * 8, 0);
            uint4* oz = g_obuf + (size_t)(g * 4 + t) * 12288 + col * 1536 + i6;
#pragma unroll 1
            for (int k = 0; k < 24; k++) { oz[k * 64] = make_uint4(0, 0, 0, 0); __nanosleep(100); }
#pragma unroll
            for (int k = 0; k < 6; k++) {
                const int e = i6 + k * 64;
                *((uint4*)(out + (size_t)(t * 96 + g * 24 + (e >> 4)) * 1024 + col * 128) + (e & 15)) = make_uint4(0, 0, 0, 0);
            }
            bar_sync_n(4, 64);
            if (i6 == 0) { red_release(bflag, 1); mbar_arrive(sb + OFF_BAR + (BAR_GO2 + 1) * 8); }
        }
        __syncwarp();
        asm volatile("barrier.cluster.wait.aligned;" ::: "memory");
        TL_DUMP();
    } else {
        asm volatile("setmaxnreg.inc.sync.aligned.u32 160;");
        const uint32_t qpiece = sb + OFF_Q + wg * 16384;
        const int mi = lane >> 3;
        if (wg > 0) {
            float acc[48];
            proj_mainloop<false>(acc, sb, wg - 1, lane);
            if (tid == 128) TL(8);
#pragma unroll
            for (int bb = 0; bb < 2; bb++)
#pragma unroll
                for (int v = 0; v < 3; v++) {
                    const int j = 6 * bb + 2 * v;
                    char* dst = (char*)g_qbuf + (size_t)(((2 * t + bb) * 4 + g) * 2 + r) * 49152 + ((3 * mem + v) * 8 + (wg - 1) * 4 + warp) * 512 + lane * 16;
                    st_relaxed_v4(dst, pack_nz(acc[4 * j], acc[4 * j + 1]), pack_nz(acc[4 * j + 2], acc[4 * j + 3]),
                                  pack_nz(acc[4 * j + 4], acc[4 * j + 5]), pack_nz(acc[4 * j + 6], acc[4 * j + 7]));
                }
            if (tid == 128) TL(9);
        } else {
            mbar_wait(sb + OFF_BAR + (BAR_GO2 + 3) * 8, 0);
        }
        if ((tid & 127) == 0) mbar_expect_tx(sb + OFF_BAR + (BAR_XFULL + wg) * 8, 128 * 9 * 16);
        const char* qsrc = (const char*)g_qbuf + (size_t)((b * 4 + g) * 2 + r) * 49152 + (4 * wg + warp) * 4096 + lane * 16;
        {
            uint4 v[8];
            bool ok;
            do {
                probe_wait(qsrc - lane * 16 + (lane & 7) * 512);
                if (lane == 0 && warp == 0) TL(42 + wg);
                ok = true;
#pragma unroll
                for (int i = 0; i < 8; i++) v[i] = ld_relaxed_v4(qsrc + i * 512);
#pragma unroll
                for (int i = 0; i < 8; i++) ok = ok && valid4(v[i]);
            } while (!__all_sync(0xffffffffu, ok));
            const uint32_t a0 = qpiece + (16 * warp + (mi >> 1) * 8 + (lane & 7)) * 128;
#pragma unroll
            for (int i = 0; i < 8; i++)
                stsm_x4_t(a0 + (i >> 2) * 8192 + (((2 * (i & 3) + (mi & 1)) ^ (lane & 7)) << 4), v[i].x, v[i].y, v[i].z, v[i].w);
            fence_async_smem();
            if (lane == 0) mbar_arrive(sb + OFF_BAR + (BAR_GO2 + 2) * 8);
            named_sync(1 + wg);
        }
        asm volatile("barrier.cluster.wait.aligned;" ::: "memory");

        {
            const float c = 0.08838834764831845f * 1.4426950408889634f;
            float o[64];
            float m0 = 0.f, m1 = 0.f, l0 = 0.f, l1 = 0.f;
            if (lane == 0 && warp == 0) TL(10 + wg);
            const uint64_t dq = mkdesc(qpiece, 0, 1024);
#pragma unroll 1
            for (int j = 0; j < 8; j++) {
                float sc[64];
                const uint32_t kslot = (0x03142031u >> (4 * j)) & 7, vslot = (0x14203142u >> (4 * j)) & 7;
                TLC(j * 6 + 0);
                mbar_wait(sb + OFF_BAR + (BAR_FULL + kslot) * 8, (0x63u >> j) & 1);
                TLC(j * 6 + 1);
                {
                    const uint64_t dk = mkdesc(sb + OFF_RING + kslot * SLOT, 0, 1024);
                    wg_fence();
#pragma unroll
                    for (int kk = 0; kk < 8; kk++)
                        wgmma_n128_ss<0, 0>(sc, dq + (kk >> 2) * (8192 >> 4) + (kk & 3) * 2, dk + (kk >> 2) * (16384 >> 4) + (kk & 3) * 2, kk != 0);
                    wg_commit();
                    wg_wait<0>();
                    reg_fence(sc);
                }
                TLC(j * 6 + 2);
                if (lane == 0) mbar_arrive(sb + OFF_BAR + (BAR_EMPTY + kslot) * 8);
                if (j == 0) {
                    float x0 = fmaxf(sc[0], sc[1]), x1 = fmaxf(sc[2], sc[3]), y0 = fmaxf(sc[4], sc[5]), y1 = fmaxf(sc[6], sc[7]);
#pragma unroll
                    for (int i = 8; i < 64; i += 8) {
                        x0 = fmaxf(x0, fmaxf(sc[i], sc[i + 1])); x1 = fmaxf(x1, fmaxf(sc[i + 2], sc[i + 3]));
                        y0 = fmaxf(y0, fmaxf(sc[i + 4], sc[i + 5])); y1 = fmaxf(y1, fmaxf(sc[i + 6], sc[i + 7]));
                    }
                    x0 = fmaxf(x0, y0); x1 = fmaxf(x1, y1);
                    x0 = fmaxf(x0, __shfl_xor_sync(0xffffffffu, x0, 1)); x1 = fmaxf(x1, __shfl_xor_sync(0xffffffffu, x1, 1));
                    x0 = fmaxf(x0, __shfl_xor_sync(0xffffffffu, x0, 2)); x1 = fmaxf(x1, __shfl_xor_sync(0xffffffffu, x1, 2));
                    m0 = x0 * c; m1 = x1 * c;
                }
                if (j == 7 && lane == 0) mbar_arrive_remote(mapa(sb + OFF_BAR + (BAR_XFREE + wg) * 8, s ^ 1));
                uint32_t p[32];
                TLC(j * 6 + 3);
                mbar_wait(sb + OFF_BAR + (BAR_FULL + vslot) * 8, (0x73u >> j) & 1);
                TLC(j * 6 + 4);
                const uint64_t dv = mkdesc(sb + OFF_RING + vslot * SLOT, 16384, 1024);
#pragma unroll
                for (int ch = 0; ch < 2; ch++) {
#pragma unroll
                    for (int i = ch * 8; i < ch * 8 + 8; i++) {
                        const float e0 = ex2(fmaf(sc[4 * i], c, -m0)), e1 = ex2(fmaf(sc[4 * i + 1], c, -m0));
                        const float e2 = ex2(fmaf(sc[4 * i + 2], c, -m1)), e3 = ex2(fmaf(sc[4 * i + 3], c, -m1));
                        p[2 * i] = pack_bf16(e0, e1);
                        p[2 * i + 1] = pack_bf16(e2, e3);
                    }
                    wg_fence();
#pragma unroll
                    for (int kk = ch * 4; kk < ch * 4 + 4; kk++)
                        wgmma_n128_rs<1>(o, p[4 * kk], p[4 * kk + 1], p[4 * kk + 2], p[4 * kk + 3], dv + kk * (2048 >> 4), (j | kk) != 0);
                    wg_commit();
                    const uint32_t* q = p + ch * 16;
                    const uint32_t a = hadd2(hadd2(hadd2(q[0], q[2]), hadd2(q[4], q[6])), hadd2(hadd2(q[8], q[10]), hadd2(q[12], q[14])));
                    const uint32_t d = hadd2(hadd2(hadd2(q[1], q[3]), hadd2(q[5], q[7])), hadd2(hadd2(q[9], q[11]), hadd2(q[13], q[15])));
                    l0 += __uint_as_float(a << 16) + __uint_as_float(a & 0xffff0000u);
                    l1 += __uint_as_float(d << 16) + __uint_as_float(d & 0xffff0000u);
                }
                wg_wait<0>();
                reg_fence(o);
                if (lane == 0) mbar_arrive(sb + OFF_BAR + (BAR_EMPTY + vslot) * 8);
                TLC(j * 6 + 5);
            }

            if (__any_sync(0xffffffffu, !(l0 <= L_SAFE && l1 <= L_SAFE))) {
                float fo[64], fml[4];
                const size_t kvoff = (size_t)((b * 4 + g) * 2048 + s * 1024) * 256;
                const char* qs = (const char*)g_qbuf + (size_t)((b * 4 + g) * 2 + r) * 49152 + (4 * wg + warp) * 4096 + (threadIdx.x & 31) * 16;
                attention_fallback(fo, fml, qs, kc + kvoff, vc + kvoff, c);
#pragma unroll
                for (int i = 0; i < 64; i++) o[i] = fo[i];
                m0 = fml[0]; m1 = fml[1]; l0 = fml[2]; l1 = fml[3];
            }
            l0 += __shfl_xor_sync(0xffffffffu, l0, 1); l1 += __shfl_xor_sync(0xffffffffu, l1, 1);
            l0 += __shfl_xor_sync(0xffffffffu, l0, 2); l1 += __shfl_xor_sync(0xffffffffu, l1, 2);
            const int u = 4 * wg + warp;
            char* odst = (char*)g_obuf + (size_t)((g * 4 + t) * 16 + (4 * r + u / 3) * 2 + s) * 12288 + ((b & 1) * 3 + u % 3) * 2048 + lane * 16;
            if (s == 0) combine_and_store<0>(o, m0, m1, l0, l1, sb, wg, warp, lane, tid, odst);
            else combine_and_store<1>(o, m0, m1, l0, l1, sb, wg, warp, lane, tid, odst);
            if (lane == 0 && warp == 0) TL(13 + wg);
        }

        if (wg == 0) {
            const char* osrc = (const char*)g_obuf + (size_t)(g * 4 + t) * 196608 + warp * 3072 + lane * 16;
            uint4 va[12], vb[12];
            auto load = [&](uint4 (&v)[12], int n) {
#pragma unroll
                for (int y = 0; y < 12; y++) v[y] = ld_relaxed_v4(osrc + p3_kblock(2 * n + y / 6) * 12288 + (y % 6) * 512);
            };
            auto finish = [&](uint4 (&v)[12], int n) {
                while (true) {
                    bool ok = true;
#pragma unroll
                    for (int y = 0; y < 12; y++) ok = ok && valid4(v[y]);
                    if (__all_sync(0xffffffffu, ok)) break;
                    probe_wait(osrc - lane * 16 + p3_kblock(2 * n + ((lane >> 1) & 1)) * 12288 + (lane & 1) * 5 * 512);
                    load(v, n);
                }
#pragma unroll
                for (int h = 0; h < 2; h++) {
                    const int f = 32 + 2 * n + h, slot = f % NSLOT;
                    mbar_wait(sb + OFF_BAR + (BAR_EMPTY + slot) * 8, ((f / NSLOT) & 1) ^ 1);
#pragma unroll
                    for (int y = 0; y < 6; y++) {
                        const int z = warp * 6 + y;
                        const uint32_t a = sb + OFF_RING + slot * SLOT + 16384 + ((z >> 2) * 16 + (mi & 1) * 8 + (lane & 7)) * 128 +
                                           (((2 * (z & 3) + (mi >> 1)) ^ (lane & 7)) << 4);
                        stsm_x4(a, v[6 * h + y].x, v[6 * h + y].y, v[6 * h + y].z, v[6 * h + y].w);
                    }
                    fence_async_smem();
                    __syncwarp();
                    if (lane == 0) mbar_arrive(sb + OFF_BAR + (BAR_OFULL + slot) * 8);
                }
                if (n == 0 && tid == 0) TL(4);
                if (n == 7 && tid == 0) TL(5);
            };
            probe_wait(osrc - lane * 16 + p3_kblock((lane >> 1) & 1) * 12288 + (lane & 1) * 5 * 512);
            load(va, 0);
#pragma unroll
            for (int n = 0; n < 8; n += 2) {
                load(vb, n + 1);
                finish(va, n);
                if (n + 2 < 8) load(va, n + 2);
                finish(vb, n + 1);
            }
        } else {
            float acc[48];
            proj_mainloop<true>(acc, sb, wg - 1, lane);
            if (tid == 128) TL(40);
            named_sync(1 + wg);
            const uint32_t a0 = qpiece + ((mi >> 1) * 8 + (lane & 7)) * 128 + (((2 * warp + (mi & 1)) ^ (lane & 7)) << 4);
#pragma unroll
            for (int j = 0; j < 12; j += 2)
                stsm_x4_t(a0 + j * 1024, pack_bf16(acc[4 * j], acc[4 * j + 1]), pack_bf16(acc[4 * j + 2], acc[4 * j + 3]),
                          pack_bf16(acc[4 * j + 4], acc[4 * j + 5]), pack_bf16(acc[4 * j + 6], acc[4 * j + 7]));
            fence_async_smem();
            named_sync(1 + wg);
            if (warp == 0 && elect_one()) {
                tma_reduce_add_2d(&tm_out, col * 128 + (wg - 1) * 64, t * 96, qpiece);
                bulk_commit();
                bulk_wait0_read();
                if (wg == 1) TL(41);
            }
            __syncwarp();
        }
        TL_DUMP();
    }
}

typedef CUresult (*EncodeFn)(CUtensorMap*, CUtensorMapDataType, cuuint32_t, void*, const cuuint64_t*, const cuuint64_t*,
                             const cuuint32_t*, const cuuint32_t*, CUtensorMapInterleave, CUtensorMapSwizzle,
                             CUtensorMapL2promotion, CUtensorMapFloatOOBfill);

void make_map(EncodeFn enc, CUtensorMap* m, const void* ptr, int rank, uint64_t rows, uint64_t cols, uint32_t box_rows) {
    cuuint64_t dims[3] = {rank == 2 ? cols : 64, rows, cols / 64};
    cuuint64_t strides[2] = {cols * 2, 128};
    cuuint32_t box[3] = {64, box_rows, 2};
    cuuint32_t es[3] = {1, 1, 1};
    enc(m, CU_TENSOR_MAP_DATA_TYPE_BFLOAT16, rank, const_cast<void*>(ptr), dims, strides, box, es, CU_TENSOR_MAP_INTERLEAVE_NONE,
        CU_TENSOR_MAP_SWIZZLE_128B, CU_TENSOR_MAP_L2_PROMOTION_L2_256B, CU_TENSOR_MAP_FLOAT_OOB_FILL_NONE);
}

}

extern "C" void kernel_launch(void* const* d_in, const int* in_sizes, int n_in, void* d_out, int out_size) {
    (void)in_sizes; (void)n_in; (void)out_size;
    static EncodeFn enc = nullptr;
    if (!enc) {
        void* fn = nullptr;
        cudaDriverEntryPointQueryResult qr;
        cudaGetDriverEntryPoint("cuTensorMapEncodeTiled", &fn, cudaEnableDefault, &qr);
        enc = (EncodeFn)fn;
        cudaFuncSetAttribute(gqa_fused_kernel, cudaFuncAttributeMaxDynamicSharedMemorySize, SMEM_TOTAL);
    }
    CUtensorMap tx, twq, tk, tv, two, tout;
    make_map(enc, &tx, d_in[0], 2, 384, 1024, 96);
    make_map(enc, &tk, d_in[1], 3, 65536, 128, 128);
    make_map(enc, &tv, d_in[2], 2, 65536, 128, 128);
    make_map(enc, &twq, d_in[3], 3, 1024, 4096, 64);
    make_map(enc, &two, d_in[4], 3, 4096, 1024, 64);
    make_map(enc, &tout, d_out, 2, 384, 1024, 48);
    gqa_fused_kernel<<<NCTA + 4, NTHREADS, SMEM_TOTAL, cudaStreamPerThread>>>(tx, twq, tk, tv, two, tout, (__nv_bfloat16*)d_out,
        (const char*)d_in[3], (const char*)d_in[1], (const char*)d_in[2], (const char*)d_in[4]);
}
```

```cpp
#include <cuda_runtime.h>
#include <cuda_bf16.h>
#include <cuda.h>
#include <stdint.h>

namespace {

constexpr int NCTA = 128;
constexpr int NTHREADS = 512;
constexpr int SLOT = 32768;
constexpr int NSLOT = 5;
constexpr int OFF_ZERO = 0;
constexpr int OFF_Q = 8192;
constexpr int OFF_ML = OFF_Q + 49152;
constexpr int OFF_RING = OFF_ML + 6144;
constexpr int OFF_BAR = OFF_RING + NSLOT * SLOT;
constexpr int SMEM_BYTES = OFF_BAR + 576;
constexpr int NS1 = 6, OFF_X1 = 38912;
constexpr int NW3 = 9, NO3 = 6;
constexpr int BAR_FULL = 0, BAR_EMPTY = 5,
              BAR_FULL1 = 10, BAR_EMPTY1 = 16, BAR_EMPTY3 = 22,
              BAR_XFREE = 28, BAR_CDONE = 31,
              BAR_GO2 = 34,
              BAR_ONES = 35, BAR_XFULL = 35, BAR_XML = 38, BAR_QFULL = 41, BAR_QFREE = 44, BAR_BOK = 46, BAR_GRP = 47,
              BAR_FULL3 = 49, BAR_OFULL = 55, BAR_WFULL = 61, BAR_END = 70;

constexpr unsigned B_CNT = 64;
#define PLACE 1
#define SCHED 3
#define ARR_CH 1
#define NCHK 2
#define CHB 0x850
#define WSTEP 2
#define GO2_AT 9
#define CLR_GAP 500
#define H_SEQ 0x765410
#define H_KV_N 6
#define H_START 2000
#define H_KV_INT 500
#define H_WO_START 26000
#define H_WO_INT 500
#define RMAP 0
#define H_W0 16
#define H_WSTART 1000
#define H_WINT 0
#define H_X 1
#define KV_GAP 600
#define SKEW3 0
constexpr int SPIN_LIMIT = 1 << 22;
constexpr float SCALE_LOG2E = 0.08838834764831845f * 1.4426950408889634f;
constexpr float L_SAFE = 1.0995116e12f;

__device__ uint4 g_oimg[16 * 16 * 12288 / 16];
__device__ unsigned g_bflag[2 * 32];

__device__ __forceinline__ void TL(int) {}
__device__ __forceinline__ void TLP(int, uint32_t, int) {}
#define TLC(idx)
#define TLF(idx)
#define TLPF(c, sb, idx)
#define STALL_BEGIN()
#define STALL_END(idx)
#define TL_INIT()
#define TL_DUMP()
#define TL_DONE()
constexpr int SMEM_TOTAL = SMEM_BYTES;

__device__ __forceinline__ uint32_t smem_u32(const void* p) { return (uint32_t)__cvta_generic_to_shared(p); }
__device__ __forceinline__ void mbar_init(uint32_t bar, uint32_t cnt) {
    asm volatile("mbarrier.init.shared::cta.b64 [%0], %1;" ::"r"(bar), "r"(cnt) : "memory");
}
__device__ __forceinline__ void mbar_expect_tx(uint32_t bar, uint32_t bytes) {
    asm volatile("mbarrier.arrive.expect_tx.shared::cta.b64 _, [%0], %1;" ::"r"(bar), "r"(bytes) : "memory");
}
__device__ __forceinline__ void mbar_arrive(uint32_t bar) {
    asm volatile("mbarrier.arrive.shared::cta.b64 _, [%0];" ::"r"(bar) : "memory");
}
__device__ __forceinline__ void mbar_arrive_cnt(uint32_t bar, uint32_t cnt) {
    asm volatile("mbarrier.arrive.shared::cta.b64 _, [%0], %1;" ::"r"(bar), "r"(cnt) : "memory");
}
__device__ __forceinline__ void mbar_arrive_remote(uint32_t cluster_addr) {
    asm volatile("fence.release.sync_restrict::shared::cta.cluster;\n"
                 "mbarrier.arrive.relaxed.cluster.shared::cluster.b64 _, [%0];" ::"r"(cluster_addr) : "memory");
}
#define SPIN_GUARD(it) asm volatile("{\n.reg .pred q;\nsetp.gt.s32 q, %0, %1;\n@q trap;\n}" ::"r"(it), "n"(SPIN_LIMIT));
__device__ __forceinline__ void (mbar_wait)(uint32_t bar, uint32_t parity) {
    asm volatile(
        "{\n.reg .pred p, q;\n.reg .u32 c;\nmov.u32 c, 0;\n"
        "WAIT_LOOP:\n"
        "mbarrier.try_wait.parity.shared::cta.b64 p, [%0], %1;\n"
        "@p bra WAIT_DONE;\n"
        "add.u32 c, c, 1;\nsetp.gt.u32 q, c, %2;\n@q trap;\n"
        "bra WAIT_LOOP;\n"
        "WAIT_DONE:\n}\n" ::"r"(bar), "r"(parity), "n"(SPIN_LIMIT) : "memory");
}
__device__ __forceinline__ void (mbar_wait_cluster)(uint32_t bar, uint32_t parity) {
    asm volatile(
        "{\n.reg .pred p, q;\n.reg .u32 c;\nmov.u32 c, 0;\n"
        "WAIT_LOOP:\n"
        "mbarrier.try_wait.parity.acquire.cluster.shared::cta.b64 p, [%0], %1;\n"
        "@p bra WAIT_DONE;\n"
        "add.u32 c, c, 1;\nsetp.gt.u32 q, c, %2;\n@q trap;\n"
        "bra WAIT_LOOP;\n"
        "WAIT_DONE:\n}\n" ::"r"(bar), "r"(parity), "n"(SPIN_LIMIT) : "memory");
}
__device__ __forceinline__ bool elect_one() {
    uint32_t el;
    asm volatile("{\n.reg .pred p;\nelect.sync _|p, 0xffffffff;\nselp.u32 %0, 1, 0, p;\n}" : "=r"(el));
    return el != 0;
}
__device__ __forceinline__ void prefetch_tmap(const CUtensorMap* tm) { asm volatile("prefetch.tensormap [%0];" ::"l"(tm) : "memory"); }
__device__ __forceinline__ uint32_t mapa(uint32_t addr, uint32_t rank) {
    uint32_t r;
    asm("mapa.shared::cluster.u32 %0, %1, %2;" : "=r"(r) : "r"(addr), "r"(rank));
    return r;
}
__device__ __forceinline__ void tma_2d(uint32_t dst, const CUtensorMap* tm, int c0, int c1, uint32_t bar) {
    asm volatile("cp.async.bulk.tensor.2d.shared::cluster.global.mbarrier::complete_tx::bytes [%0], [%1, {%3, %4}], [%2];"
                 ::"r"(dst), "l"(tm), "r"(bar), "r"(c0), "r"(c1) : "memory");
}
__device__ __forceinline__ void tma_3d(uint32_t dst, const CUtensorMap* tm, int c0, int c1, int c2, uint32_t bar) {
    asm volatile("cp.async.bulk.tensor.3d.shared::cluster.global.mbarrier::complete_tx::bytes [%0], [%1, {%3, %4, %5}], [%2];"
                 ::"r"(dst), "l"(tm), "r"(bar), "r"(c0), "r"(c1), "r"(c2) : "memory");
}
__device__ __forceinline__ void tma_4d(uint32_t dst, const CUtensorMap* tm, int c0, int c1, int c2, int c3, uint32_t bar) {
    asm volatile("cp.async.bulk.tensor.4d.shared::cluster.global.mbarrier::complete_tx::bytes [%0], [%1, {%3, %4, %5, %6}], [%2];"
                 ::"r"(dst), "l"(tm), "r"(bar), "r"(c0), "r"(c1), "r"(c2), "r"(c3) : "memory");
}
__device__ __forceinline__ void bulk_s2peer(uint32_t dst_cluster, uint32_t src, uint32_t bytes, uint32_t bar_cluster) {
    asm volatile("cp.async.bulk.shared::cluster.shared::cta.mbarrier::complete_tx::bytes [%0], [%1], %2, [%3];"
                 ::"r"(dst_cluster), "r"(src), "r"(bytes), "r"(bar_cluster) : "memory");
}
__device__ __forceinline__ void bulk_g2s(uint32_t dst, const void* src, uint32_t bytes, uint32_t bar) {
    asm volatile("cp.async.bulk.shared::cluster.global.mbarrier::complete_tx::bytes [%0], [%1], %2, [%3];"
                 ::"r"(dst), "l"(src), "r"(bytes), "r"(bar) : "memory");
}
__device__ __forceinline__ void bulk_s2g(void* dst, uint32_t src, uint32_t bytes) {
    asm volatile("cp.async.bulk.global.shared::cta.bulk_group [%0], [%1], %2;" ::"l"(dst), "r"(src), "r"(bytes) : "memory");
}
__device__ __forceinline__ void tma_reduce_add_2d(const CUtensorMap* tm, int c0, int c1, uint32_t src) {
    asm volatile("cp.reduce.async.bulk.tensor.2d.global.shared::cta.add.tile.bulk_group [%0, {%2, %3}], [%1];"
                 ::"l"(tm), "r"(src), "r"(c0), "r"(c1) : "memory");
}
__device__ __forceinline__ void l2_prefetch(const void* src, uint32_t bytes) {
    asm volatile("cp.async.bulk.prefetch.L2.global [%0], %1;" ::"l"(src), "r"(bytes) : "memory");
}
__device__ __forceinline__ uint32_t clock32() {
    uint32_t c;
    asm volatile("mov.u32 %0, %%clock;" : "=r"(c)::"memory");
    return c;
}
__device__ __forceinline__ void bulk_commit() { asm volatile("cp.async.bulk.commit_group;" ::: "memory"); }
__device__ __forceinline__ void bulk_wait0() { asm volatile("cp.async.bulk.wait_group 0;" ::: "memory"); }
__device__ __forceinline__ void bulk_wait0_read() { asm volatile("cp.async.bulk.wait_group.read 0;" ::: "memory"); }
__device__ __forceinline__ void fence_async_smem() { asm volatile("fence.proxy.async.shared::cta;" ::: "memory"); }
__device__ __forceinline__ void fence_async_all() { asm volatile("fence.proxy.async;" ::: "memory"); }
__device__ __forceinline__ void red_release(unsigned* p, unsigned v) {
    asm volatile("red.release.gpu.global.add.u32 [%0], %1;" ::"l"(p), "r"(v) : "memory");
}
__device__ __forceinline__ unsigned ld_acquire(const unsigned* p) {
    unsigned v;
    asm volatile("ld.acquire.gpu.global.u32 %0, [%1];" : "=r"(v) : "l"(p) : "memory");
    return v;
}
__device__ __forceinline__ unsigned ld_relaxed(const unsigned* p) {
    unsigned v;
    asm volatile("ld.relaxed.gpu.global.u32 %0, [%1];" : "=r"(v) : "l"(p) : "memory");
    return v;
}
__device__ __forceinline__ void (flag_wait)(const unsigned* p, unsigned target) {
    asm volatile(
        "{\n.reg .pred p, q;\n.reg .u32 c, v;\nmov.u32 c, 0;\n"
        "FLAG_LOOP:\n"
        "ld.acquire.gpu.global.u32 v, [%0];\n"
        "sub.u32 v, v, %1;\nsetp.ge.s32 p, v, 0;\n"
        "@p bra FLAG_DONE;\n"
        "add.u32 c, c, 1;\nsetp.gt.u32 q, c, %2;\n@q trap;\n"
        "bra FLAG_LOOP;\n"
        "FLAG_DONE:\n}\n" ::"l"(p), "r"(target), "n"(SPIN_LIMIT) : "memory");
}
__device__ __forceinline__ void named_sync(int id) { asm volatile("bar.sync %0, 128;" ::"r"(id) : "memory"); }
__device__ __forceinline__ void wg_fence() { asm volatile("wgmma.fence.sync.aligned;" ::: "memory"); }
__device__ __forceinline__ void wg_commit() { asm volatile("wgmma.commit_group.sync.aligned;" ::: "memory"); }
template <int N> __device__ __forceinline__ void wg_wait() { asm volatile("wgmma.wait_group.sync.aligned %0;" ::"n"(N) : "memory"); }
template <int N> __device__ __forceinline__ void reg_fence(float (&d)[N]) {
#pragma unroll
    for (int i = 0; i < N; i++) asm volatile("" : "+f"(d[i])::"memory");
}
__device__ __forceinline__ uint64_t mkdesc(uint32_t addr, uint32_t lbo, uint32_t sbo) {
    return (uint64_t)((addr & 0x3FFFF) >> 4) | ((uint64_t)(lbo >> 4) << 16) | ((uint64_t)(sbo >> 4) << 32) | (1ull << 62);
}
__device__ __forceinline__ uint32_t pack_bf16(float lo, float hi) {
    uint32_t r;
    asm("cvt.rn.bf16x2.f32 %0, %1, %2;" : "=r"(r) : "f"(hi), "f"(lo));
    return r;
}
__device__ __forceinline__ uint32_t hadd2(uint32_t a, uint32_t b) {
    uint32_t r;
    asm("add.rn.bf16x2 %0, %1, %2;" : "=r"(r) : "r"(a), "r"(b));
    return r;
}
__device__ __forceinline__ float ex2(float x) {
    float y;
    asm("ex2.approx.ftz.f32 %0, %1;" : "=f"(y) : "f"(x));
    return y;
}
__device__ __forceinline__ void stsm_x4(uint32_t addr, uint32_t r0, uint32_t r1, uint32_t r2, uint32_t r3) {
    asm volatile("stmatrix.sync.aligned.m8n8.x4.shared.b16 [%0], {%1, %2, %3, %4};" ::"r"(addr), "r"(r0), "r"(r1), "r"(r2), "r"(r3) : "memory");
}
__device__ __forceinline__ void stsm_x4_t(uint32_t addr, uint32_t r0, uint32_t r1, uint32_t r2, uint32_t r3) {
    asm volatile("stmatrix.sync.aligned.m8n8.x4.trans.shared.b16 [%0], {%1, %2, %3, %4};" ::"r"(addr), "r"(r0), "r"(r1), "r"(r2), "r"(r3) : "memory");
}
__device__ __forceinline__ void st_async_v4(uint32_t addr, float a, float b, float c, float d, uint32_t bar) {
    asm volatile("st.async.weak.shared::cluster.mbarrier::complete_tx::bytes.v4.f32 [%0], {%1, %2, %3, %4}, [%5];"
                 ::"r"(addr), "f"(a), "f"(b), "f"(c), "f"(d), "r"(bar) : "memory");
}
__device__ __forceinline__ void st_async_v4u(uint32_t addr, uint32_t a, uint32_t b, uint32_t c, uint32_t d, uint32_t bar) {
    asm volatile("st.async.weak.shared::cluster.mbarrier::complete_tx::bytes.v4.b32 [%0], {%1, %2, %3, %4}, [%5];"
                 ::"r"(addr), "r"(a), "r"(b), "r"(c), "r"(d), "r"(bar) : "memory");
}
__device__ __forceinline__ uint32_t lds_u32(uint32_t addr) {
    uint32_t v;
    asm volatile("ld.shared.u32 %0, [%1];" : "=r"(v) : "r"(addr) : "memory");
    return v;
}
__device__ __forceinline__ float rcp_fast(float x) {
    float y;
    asm("rcp.approx.ftz.f32 %0, %1;" : "=f"(y) : "f"(x));
    return y;
}
__device__ __forceinline__ float bf_lo(uint32_t w) { return __uint_as_float(w << 16); }
__device__ __forceinline__ float bf_hi(uint32_t w) { return __uint_as_float(w & 0xffff0000u); }
__device__ __forceinline__ float4 lds_v4(uint32_t addr) {
    float4 v;
    asm volatile("ld.shared.v4.f32 {%0, %1, %2, %3}, [%4];" : "=f"(v.x), "=f"(v.y), "=f"(v.z), "=f"(v.w) : "r"(addr) : "memory");
    return v;
}

__device__ __forceinline__ uint4 ld_relaxed_v4(const void* p) {
    uint4 v;
    asm volatile("ld.relaxed.gpu.global.v4.u32 {%0, %1, %2, %3}, [%4];" : "=r"(v.x), "=r"(v.y), "=r"(v.z), "=r"(v.w) : "l"(p) : "memory");
    return v;
}
__device__ __forceinline__ void st_relaxed_v4(void* p, uint32_t a, uint32_t b, uint32_t c, uint32_t d) {
    asm volatile("st.relaxed.gpu.global.v4.u32 [%0], {%1, %2, %3, %4};" ::"l"(p), "r"(a), "r"(b), "r"(c), "r"(d) : "memory");
}
__device__ __forceinline__ uint32_t pack_nz(float lo, float hi) {
    const uint32_t w = pack_bf16(lo, hi);
    return w == 0u ? 0x80008000u : w;
}
__device__ __forceinline__ bool valid4(const uint4& v) { return min(min(v.x, v.y), min(v.z, v.w)) != 0u; }
__device__ __forceinline__ void (probe_wait)(const void* p) {
    asm volatile(
        "{\n.reg .pred p, q;\n.reg .u32 c, v;\nmov.u32 c, 0;\n"
        "PROBE_LOOP:\n"
        "ld.relaxed.gpu.global.u32 v, [%0];\n"
        "setp.ne.u32 p, v, 0;\n"
        "vote.sync.all.pred p, p, 0xffffffff;\n"
        "@p bra PROBE_DONE;\n"
        "add.u32 c, c, 1;\nsetp.gt.u32 q, c, %1;\n@q trap;\n"
        "bra PROBE_LOOP;\n"
        "PROBE_DONE:\n}\n" ::"l"(p), "n"(SPIN_LIMIT) : "memory");
}
__device__ __forceinline__ void bar_sync_n(int id, int n) { asm volatile("bar.sync %0, %1;" ::"r"(id), "r"(n) : "memory"); }
__device__ __forceinline__ void bar_arrive_n(int id, int n) { asm volatile("bar.arrive %0, %1;" ::"r"(id), "r"(n) : "memory"); }
__device__ __forceinline__ uint32_t movm_t(uint32_t a) {
    uint32_t d;
    asm volatile("movmatrix.sync.aligned.m8n8.trans.b16 %0, %1;" : "=r"(d) : "r"(a));
    return d;
}
__device__ __forceinline__ void mma_16816(float* d, uint32_t a0, uint32_t a1, uint32_t a2, uint32_t a3, uint32_t b0, uint32_t b1) {
    asm volatile("mma.sync.aligned.m16n8k16.row.col.f32.bf16.bf16.f32 {%0, %1, %2, %3}, {%4, %5, %6, %7}, {%8, %9}, {%0, %1, %2, %3};"
                 : "+f"(d[0]), "+f"(d[1]), "+f"(d[2]), "+f"(d[3]) : "r"(a0), "r"(a1), "r"(a2), "r"(a3), "r"(b0), "r"(b1));
}

template <int V> struct Int { static constexpr int value = V; };

template <int TA, int TB>
__device__ __forceinline__ void wgmma_n48_ss(float (&d)[24], uint64_t da, uint64_t db, int scale_d) {
    asm volatile("{\n.reg .pred p;\nsetp.ne.b32 p, %26, 0;\n"
        "wgmma.mma_async.sync.aligned.m64n48k16.f32.bf16.bf16 {"
        "%0, %1, %2, %3, %4, %5, %6, %7, %8, %9, %10, %11, %12, %13, %14, %15, "
        "%16, %17, %18, %19, %20, %21, %22, %23}, "
        "%24, %25, p, 1, 1, %27, %28;\n}\n"
        : "+f"(d[0]), "+f"(d[1]), "+f"(d[2]), "+f"(d[3]), "+f"(d[4]), "+f"(d[5]), "+f"(d[6]), "+f"(d[7]),
          "+f"(d[8]), "+f"(d[9]), "+f"(d[10]), "+f"(d[11]), "+f"(d[12]), "+f"(d[13]), "+f"(d[14]), "+f"(d[15]),
          "+f"(d[16]), "+f"(d[17]), "+f"(d[18]), "+f"(d[19]), "+f"(d[20]), "+f"(d[21]), "+f"(d[22]), "+f"(d[23])
        : "l"(da), "l"(db), "r"(scale_d), "n"(TA), "n"(TB));
}
template <int TA, int TB>
__device__ __forceinline__ void wgmma_n96_ss(float (&d)[48], uint64_t da, uint64_t db, int scale_d) {
    asm volatile("{\n.reg .pred p;\nsetp.ne.b32 p, %50, 0;\n"
        "wgmma.mma_async.sync.aligned.m64n96k16.f32.bf16.bf16 {"
        "%0, %1, %2, %3, %4, %5, %6, %7, %8, %9, %10, %11, %12, %13, %14, %15, "
        "%16, %17, %18, %19, %20, %21, %22, %23, %24, %25, %26, %27, %28, %29, %30, %31, "
        "%32, %33, %34, %35, %36, %37, %38, %39, %40, %41, %42, %43, %44, %45, %46, %47}, "
        "%48, %49, p, 1, 1, %51, %52;\n}\n"
        : "+f"(d[0]), "+f"(d[1]), "+f"(d[2]), "+f"(d[3]), "+f"(d[4]), "+f"(d[5]), "+f"(d[6]), "+f"(d[7]),
          "+f"(d[8]), "+f"(d[9]), "+f"(d[10]), "+f"(d[11]), "+f"(d[12]), "+f"(d[13]), "+f"(d[14]), "+f"(d[15]),
          "+f"(d[16]), "+f"(d[17]), "+f"(d[18]), "+f"(d[19]), "+f"(d[20]), "+f"(d[21]), "+f"(d[22]), "+f"(d[23]),
          "+f"(d[24]), "+f"(d[25]), "+f"(d[26]), "+f"(d[27]), "+f"(d[28]), "+f"(d[29]), "+f"(d[30]), "+f"(d[31]),
          "+f"(d[32]), "+f"(d[33]), "+f"(d[34]), "+f"(d[35]), "+f"(d[36]), "+f"(d[37]), "+f"(d[38]), "+f"(d[39]),
          "+f"(d[40]), "+f"(d[41]), "+f"(d[42]), "+f"(d[43]), "+f"(d[44]), "+f"(d[45]), "+f"(d[46]), "+f"(d[47])
        : "l"(da), "l"(db), "r"(scale_d), "n"(TA), "n"(TB));
}
template <int TA, int TB>
__device__ __forceinline__ void wgmma_n128_ss(float (&d)[64], uint64_t da, uint64_t db, int scale_d) {
    asm volatile("{\n.reg .pred p;\nsetp.ne.b32 p, %66, 0;\n"
        "wgmma.mma_async.sync.aligned.m64n128k16.f32.bf16.bf16 {"
        "%0, %1, %2, %3, %4, %5, %6, %7, %8, %9, %10, %11, %12, %13, %14, %15, "
        "%16, %17, %18, %19, %20, %21, %22, %23, %24, %25, %26, %27, %28, %29, %30, %31, "
        "%32, %33, %34, %35, %36, %37, %38, %39, %40, %41, %42, %43, %44, %45, %46, %47, "
        "%48, %49, %50, %51, %52, %53, %54, %55, %56, %57, %58, %59, %60, %61, %62, %63}, "
        "%64, %65, p, 1, 1, %67, %68;\n}\n"
        : "+f"(d[0]), "+f"(d[1]), "+f"(d[2]), "+f"(d[3]), "+f"(d[4]), "+f"(d[5]), "+f"(d[6]), "+f"(d[7]),
          "+f"(d[8]), "+f"(d[9]), "+f"(d[10]), "+f"(d[11]), "+f"(d[12]), "+f"(d[13]), "+f"(d[14]), "+f"(d[15]),
          "+f"(d[16]), "+f"(d[17]), "+f"(d[18]), "+f"(d[19]), "+f"(d[20]), "+f"(d[21]), "+f"(d[22]), "+f"(d[23]),
          "+f"(d[24]), "+f"(d[25]), "+f"(d[26]), "+f"(d[27]), "+f"(d[28]), "+f"(d[29]), "+f"(d[30]), "+f"(d[31]),
          "+f"(d[32]), "+f"(d[33]), "+f"(d[34]), "+f"(d[35]), "+f"(d[36]), "+f"(d[37]), "+f"(d[38]), "+f"(d[39]),
          "+f"(d[40]), "+f"(d[41]), "+f"(d[42]), "+f"(d[43]), "+f"(d[44]), "+f"(d[45]), "+f"(d[46]), "+f"(d[47]),
          "+f"(d[48]), "+f"(d[49]), "+f"(d[50]), "+f"(d[51]), "+f"(d[52]), "+f"(d[53]), "+f"(d[54]), "+f"(d[55]),
          "+f"(d[56]), "+f"(d[57]), "+f"(d[58]), "+f"(d[59]), "+f"(d[60]), "+f"(d[61]), "+f"(d[62]), "+f"(d[63])
        : "l"(da), "l"(db), "r"(scale_d), "n"(TA), "n"(TB));
}
template <int TB>
__device__ __forceinline__ void wgmma_n128_rs(float (&d)[64], uint32_t a0, uint32_t a1, uint32_t a2, uint32_t a3, uint64_t db, int scale_d) {
    asm volatile("{\n.reg .pred p;\nsetp.ne.b32 p, %69, 0;\n"
        "wgmma.mma_async.sync.aligned.m64n128k16.f32.bf16.bf16 {"
        "%0, %1, %2, %3, %4, %5, %6, %7, %8, %9, %10, %11, %12, %13, %14, %15, "
        "%16, %17, %18, %19, %20, %21, %22, %23, %24, %25, %26, %27, %28, %29, %30, %31, "
        "%32, %33, %34, %35, %36, %37, %38, %39, %40, %41, %42, %43, %44, %45, %46, %47, "
        "%48, %49, %50, %51, %52, %53, %54, %55, %56, %57, %58, %59, %60, %61, %62, %63}, "
        "{%64, %65, %66, %67}, %68, p, 1, 1, %70;\n}\n"
        : "+f"(d[0]), "+f"(d[1]), "+f"(d[2]), "+f"(d[3]), "+f"(d[4]), "+f"(d[5]), "+f"(d[6]), "+f"(d[7]),
          "+f"(d[8]), "+f"(d[9]), "+f"(d[10]), "+f"(d[11]), "+f"(d[12]), "+f"(d[13]), "+f"(d[14]), "+f"(d[15]),
          "+f"(d[16]), "+f"(d[17]), "+f"(d[18]), "+f"(d[19]), "+f"(d[20]), "+f"(d[21]), "+f"(d[22]), "+f"(d[23]),
          "+f"(d[24]), "+f"(d[25]), "+f"(d[26]), "+f"(d[27]), "+f"(d[28]), "+f"(d[29]), "+f"(d[30]), "+f"(d[31]),
          "+f"(d[32]), "+f"(d[33]), "+f"(d[34]), "+f"(d[35]), "+f"(d[36]), "+f"(d[37]), "+f"(d[38]), "+f"(d[39]),
          "+f"(d[40]), "+f"(d[41]), "+f"(d[42]), "+f"(d[43]), "+f"(d[44]), "+f"(d[45]), "+f"(d[46]), "+f"(d[47]),
          "+f"(d[48]), "+f"(d[49]), "+f"(d[50]), "+f"(d[51]), "+f"(d[52]), "+f"(d[53]), "+f"(d[54]), "+f"(d[55]),
          "+f"(d[56]), "+f"(d[57]), "+f"(d[58]), "+f"(d[59]), "+f"(d[60]), "+f"(d[61]), "+f"(d[62]), "+f"(d[63])
        : "r"(a0), "r"(a1), "r"(a2), "r"(a3), "l"(db), "r"(scale_d), "n"(TB));
}

template <bool P3>
__device__ __forceinline__ void proj_mainloop(float (&acc)[48], uint32_t sb, int half, int lane) {
    constexpr int F0 = P3 ? 32 : 0;
    int slot = F0 % NSLOT, par = (F0 / NSLOT) & 1, opar = 0;
    int prev = 0;
#pragma unroll 1
    for (int kb = 0; kb < 16; kb++) {
        mbar_wait(sb + OFF_BAR + (BAR_FULL + slot) * 8, par);
        if (P3) mbar_wait(sb + OFF_BAR + (BAR_OFULL + slot) * 8, opar);
        const uint32_t st = __shfl_sync(0xffffffffu, sb + OFF_RING + slot * SLOT, 0);
        const uint64_t da = mkdesc(st + half * 8192, 0, 1024);
        const uint64_t db = mkdesc(st + 16384, 0, 1024);
        wg_fence();
#pragma unroll
        for (int kk = 0; kk < 4; kk++) wgmma_n96_ss<1, 0>(acc, da + kk * (2048 >> 4), db + kk * (32 >> 4), (kb | kk) != 0);
        wg_commit();
        if (threadIdx.x == 128 && (kb & 1) == 0) TL((P3 ? 56 : 48) + kb / 2);
        if (kb > 0) {
            wg_wait<1>();
            if (lane == 0) mbar_arrive_cnt(sb + OFF_BAR + (BAR_EMPTY + prev) * 8, 2 - half);
        }
        prev = slot;
        if (++slot == NSLOT) { slot = 0; par ^= 1; }
        if (slot == F0 % NSLOT) opar ^= 1;
    }
    wg_wait<0>();
    reg_fence(acc);
    if (lane == 0) mbar_arrive_cnt(sb + OFF_BAR + (BAR_EMPTY + prev) * 8, 2 - half);
}

__device__ __noinline__ void attention_fallback(float* o, float* ml, const char* qsrc, const char* kptr, const char* vptr, float c) {
    const int lane = threadIdx.x & 31;
    uint32_t q[32];
#pragma unroll
    for (int i = 0; i < 8; i++) {
        const uint4 v = ld_relaxed_v4(qsrc + i * 512);
        q[4 * i] = movm_t(v.x); q[4 * i + 2] = movm_t(v.y); q[4 * i + 1] = movm_t(v.z); q[4 * i + 3] = movm_t(v.w);
    }
    float acc[64];
#pragma unroll
    for (int i = 0; i < 64; i++) acc[i] = 0.f;
    float m0 = -INFINITY, m1 = -INFINITY, l0 = 0.f, l1 = 0.f;
#pragma unroll 1
    for (int k0 = 0; k0 < 1024; k0 += 16) {
        float sc[8];
#pragma unroll
        for (int i = 0; i < 8; i++) sc[i] = 0.f;
#pragma unroll
        for (int nb = 0; nb < 2; nb++)
#pragma unroll
            for (int kk = 0; kk < 8; kk++) {
                const char* kp = kptr + (size_t)(k0 + nb * 8 + (lane >> 2)) * 256 + kk * 32 + (lane & 3) * 4;
                mma_16816(sc + 4 * nb, q[4 * kk], q[4 * kk + 1], q[4 * kk + 2], q[4 * kk + 3], *(const uint32_t*)kp, *(const uint32_t*)(kp + 16));
            }
        float n0 = fmaxf(fmaxf(sc[0], sc[1]), fmaxf(sc[4], sc[5])) * c, n1 = fmaxf(fmaxf(sc[2], sc[3]), fmaxf(sc[6], sc[7])) * c;
        n0 = fmaxf(n0, __shfl_xor_sync(0xffffffffu, n0, 1)); n1 = fmaxf(n1, __shfl_xor_sync(0xffffffffu, n1, 1));
        n0 = fmaxf(n0, __shfl_xor_sync(0xffffffffu, n0, 2)); n1 = fmaxf(n1, __shfl_xor_sync(0xffffffffu, n1, 2));
        n0 = fmaxf(n0, m0); n1 = fmaxf(n1, m1);
        const float al0 = ex2(m0 - n0), al1 = ex2(m1 - n1);
        m0 = n0; m1 = n1;
        float e[8];
#pragma unroll
        for (int i = 0; i < 8; i++) e[i] = ex2(fmaf(sc[i], c, (i & 2) ? -n1 : -n0));
        l0 = l0 * al0 + (e[0] + e[1]) + (e[4] + e[5]);
        l1 = l1 * al1 + (e[2] + e[3]) + (e[6] + e[7]);
        const uint32_t p0 = pack_bf16(e[0], e[1]), p1 = pack_bf16(e[2], e[3]), p2 = pack_bf16(e[4], e[5]), p3 = pack_bf16(e[6], e[7]);
#pragma unroll
        for (int nb = 0; nb < 16; nb++) {
            const unsigned short* vp = (const unsigned short*)(vptr + (size_t)(k0 + (lane & 3) * 2) * 256) + nb * 8 + (lane >> 2);
            const uint32_t b0 = vp[0] | ((uint32_t)vp[128] << 16), b1 = vp[8 * 128] | ((uint32_t)vp[9 * 128] << 16);
            acc[4 * nb] *= al0; acc[4 * nb + 1] *= al0; acc[4 * nb + 2] *= al1; acc[4 * nb + 3] *= al1;
            mma_16816(acc + 4 * nb, p0, p1, p2, p3, b0, b1);
        }
    }
#pragma unroll
    for (int i = 0; i < 64; i++) o[i] = acc[i];
    ml[0] = m0; ml[1] = m1; ml[2] = l0; ml[3] = l1;
}

template <int S>
__device__ __forceinline__ void combine_and_store(float (&o)[64], float m0, float m1, float l0, float l1, uint32_t sb,
                                                  int wg, int warp, int lane, int tid, char* odst) {
    constexpr int KEEP = S * 32, SEND = 32 - KEEP;
    const uint32_t wbuf = sb + OFF_Q + wg * 16384 + warp * 4096;
    const uint32_t peer_buf = mapa(wbuf + lane * 16, S ^ 1);
    const uint32_t peer_ml = mapa(sb + OFF_ML + tid * 16, S ^ 1);
    const uint32_t peer_bar = mapa(sb + OFF_BAR + (BAR_XFULL + wg) * 8, S ^ 1);
    mbar_wait_cluster(sb + OFF_BAR + (BAR_XFREE + wg) * 8, 0);
    st_async_v4(peer_ml, m0, m1, l0, l1, peer_bar);
#pragma unroll
    for (int i = 0; i < 8; i++)
        st_async_v4(peer_buf + i * 512, o[SEND + 4 * i], o[SEND + 4 * i + 1], o[SEND + 4 * i + 2], o[SEND + 4 * i + 3], peer_bar);
    mbar_wait_cluster(sb + OFF_BAR + (BAR_XFULL + wg) * 8, 0);
    const float4 pml = lds_v4(sb + OFF_ML + tid * 16);
    const float mm0 = fmaxf(m0, pml.x), mm1 = fmaxf(m1, pml.y);
    float a0 = ex2(m0 - mm0), b0 = ex2(pml.x - mm0);
    float a1 = ex2(m1 - mm1), b1 = ex2(pml.y - mm1);
    const float inv0 = 1.0f / (a0 * l0 + b0 * pml.z), inv1 = 1.0f / (a1 * l1 + b1 * pml.w);
    a0 *= inv0; b0 *= inv0; a1 *= inv1; b1 *= inv1;
#pragma unroll
    for (int q = 0; q < 4; q++) {
        const float4 v = lds_v4(wbuf + lane * 16 + (2 * q) * 512), w = lds_v4(wbuf + lane * 16 + (2 * q + 1) * 512);
        const int i = KEEP + 8 * q;
        st_relaxed_v4(odst + q * 512, pack_nz(o[i] * a0 + v.x * b0, o[i + 1] * a0 + v.y * b0), pack_nz(o[i + 2] * a1 + v.z * b1, o[i + 3] * a1 + v.w * b1),
                      pack_nz(o[i + 4] * a0 + w.x * b0, o[i + 5] * a0 + w.y * b0), pack_nz(o[i + 6] * a1 + w.z * b1, o[i + 7] * a1 + w.w * b1));
    }
}

__device__ __forceinline__ int p3_kblock(int n) { return (n >> 2) * 2 + (n & 1) + ((n >> 1) & 1) * 8; }

__global__ void __cluster_dims__(2, 1, 1) __launch_bounds__(NTHREADS, 1)
gqa_fused_kernel(const __grid_constant__ CUtensorMap tm_x, const __grid_constant__ CUtensorMap tm_wq,
                 const __grid_constant__ CUtensorMap tm_k, const __grid_constant__ CUtensorMap tm_v,
                 const __grid_constant__ CUtensorMap tm_wo, const __grid_constant__ CUtensorMap tm_out,
                 __nv_bfloat16* __restrict__ out, const char* __restrict__ wq, const char* __restrict__ kc,
                 const char* __restrict__ vc, const char* __restrict__ wo) {
    extern __shared__ __align__(1024) unsigned char smem[];
    uint32_t sb = smem_u32(smem);
    asm volatile("mov.u32 %0, %0;" : "+r"(sb));
    const int tid = threadIdx.x, lane = tid & 31;
    const int wg = __shfl_sync(0xffffffffu, tid >> 7, 0), warp = __shfl_sync(0xffffffffu, (tid >> 5) & 3, 0);
    const int bid = blockIdx.x;
    const int mem = bid & 3, r = (bid >> 2) & 1, t = (bid >> 3) & 3, g = bid >> 5;
    const int s = mem & 1, b = 2 * t + (mem >> 1), col = bid & 7;
    const int head = g * 8 + r * 4 + mem;

    TL_INIT();
    if (wg == 3 && warp == 0) {
        if (elect_one()) {
            TL(0);
#pragma unroll
            for (int i = 0; i < NSLOT; i++) {
                mbar_init(sb + OFF_BAR + (BAR_FULL + i) * 8, 1);
                mbar_init(sb + OFF_BAR + (BAR_EMPTY + i) * 8, 12);
                mbar_init(sb + OFF_BAR + (BAR_OFULL + i) * 8, 4);
            }
#pragma unroll
            for (int i = 0; i < 3; i++) {
                mbar_init(sb + OFF_BAR + (BAR_XFREE + i) * 8, 4);
                mbar_init(sb + OFF_BAR + (BAR_XFULL + i) * 8, 1);
            }
            mbar_init(sb + OFF_BAR + BAR_GO2 * 8, 1);
            mbar_init(sb + OFF_BAR + (BAR_GO2 + 1) * 8, 1);
            mbar_init(sb + OFF_BAR + (BAR_GO2 + 2) * 8, 12);
            mbar_init(sb + OFF_BAR + (BAR_GO2 + 3) * 8, 1);
            asm volatile("fence.mbarrier_init.release.cluster;" ::: "memory");
            fence_async_smem();
#pragma unroll
            for (int f = 0; f < NSLOT; f++) {
                const uint32_t full = sb + OFF_BAR + (BAR_FULL + f) * 8, st = sb + OFF_RING + f * SLOT;
                mbar_expect_tx(full, 28672);
                tma_3d(st, &tm_wq, 0, f * 64, head * 2, full);
                tma_2d(st + 16384, &tm_x, f * 64, t * 96, full);
            }
#pragma unroll
            for (int f = NSLOT; f < NSLOT + PF_DIST; f++) l2_prefetch(wq + (size_t)f * 524288 + bid * 4096, 4096);
            TL(1);
        }
    } else if (wg == 3 && warp == 1) {
        if (elect_one()) { prefetch_tmap(&tm_k); prefetch_tmap(&tm_v); prefetch_tmap(&tm_wo); prefetch_tmap(&tm_out); }
    }
    __syncthreads();
    asm volatile("barrier.cluster.arrive.relaxed.aligned;" ::: "memory");

    if (wg == 3) {
        asm volatile("setmaxnreg.dec.sync.aligned.u32 32;");
        if (warp == 0) {
            if (elect_one()) {
                uint32_t bar = sb + OFF_BAR, st = sb + OFF_RING;
                uint32_t par = 0;
                auto advance = [&]() {
                    bar += 8; st += SLOT;
                    if (bar == sb + OFF_BAR + NSLOT * 8) { bar = sb + OFF_BAR; st = sb + OFF_RING; par ^= 1; }
                };
#pragma unroll 1
                for (int f = NSLOT; f < 16; f++) {
                    if (f == 15) {
                        mbar_wait(sb + OFF_BAR + (BAR_GO2 + 1) * 8, 0);
                        unsigned at;
                        asm volatile("ld.shared.u32 %0, [%1];" : "=r"(at) : "r"(sb + OFF_ZT) : "memory");
                        flag_wait(g_aflag + (bid >> 2) * 32, at);
                        mbar_arrive(sb + OFF_BAR + (BAR_GO2 + 3) * 8);
                    }
                    mbar_wait(bar + BAR_EMPTY * 8, par);
                    mbar_expect_tx(bar, 28672);
                    tma_3d(st, &tm_wq, 0, f * 64, head * 2, bar);
                    tma_2d(st + 16384, &tm_x, f * 64, t * 96, bar);
                    if (f + PF_DIST < 16) l2_prefetch(wq + (size_t)(f + PF_DIST) * 524288 + bid * 4096, 4096);
                    advance();
                }
                const int kvrow = (b * 4 + g) * 2048 + s * 1024;
                TL(2);
#pragma unroll 1
                for (int f = 0; f < 16; f++) {
                    if (f == KV_EARLY) { mbar_wait(sb + OFF_BAR + (BAR_GO2 + 2) * 8, 0); TL(3); }
                    if (f == 8) mbar_arrive(sb + OFF_BAR + BAR_GO2 * 8);
                    if (f == 15) {
                        mbar_wait(sb + OFF_BAR + (BAR_GO2 + 1) * 8, 1);
                        unsigned bt;
                        asm volatile("ld.shared.u32 %0, [%1];" : "=r"(bt) : "r"(sb + OFF_ZT + 4) : "memory");
                        flag_wait(g_bflag + t * 32, bt);
                        fence_async_all();
                    }
                    mbar_wait(bar + BAR_EMPTY * 8, par);
                    mbar_expect_tx(bar, 32768);
                    tma_3d(st, (f & 1) ? &tm_v : &tm_k, 0, kvrow + (f >> 1) * 128, 0, bar);
                    TL(16 + f);
                    if (f >= KV_EARLY && f < NSLOT) { const uint32_t t0 = clock32(); while ((int)(clock32() - t0) < KV_GAP) ; }
                    advance();
                }
#pragma unroll 1
                for (int f = 0; f < 16; f++) {
                    mbar_wait(bar + BAR_EMPTY * 8, par);
                    mbar_expect_tx(bar, 16384);
                    tma_3d(st, &tm_wo, 0, g * 1024 + p3_kblock(f) * 64, col * 2, bar);
                    advance();
                }
                TL(6);
            }
        } else if (warp == 1) {
            if (elect_one()) {
                uint32_t next = clock32() + PF_WO_START;
                mbar_wait(sb + OFF_BAR + (BAR_GO2 + 3) * 8, 0);
                {
                    uint32_t nx = clock32() + PF_KV_DELAY;
                    const size_t kvoff = ((size_t)((b * 4 + g) * 2048 + s * 1024 + r * 64)) * 256;
#pragma unroll 1
                    for (int c = KV_EARLY * (16384 / PF_CH); c < PF_KV_END * (16384 / PF_CH); c++) {
                        const int f = c / (16384 / PF_CH);
                        while ((int)(clock32() - nx) < 0) __nanosleep(40);
                        l2_prefetch(((f & 1) ? vc : kc) + kvoff + (size_t)(f >> 1) * 32768 + (c % (16384 / PF_CH)) * PF_CH, PF_CH);
                        nx += PF_KV_INT;
                    }
                }
#pragma unroll 1
                for (int i = 0; i < 16; i++) {
                    while ((int)(clock32() - next) < 0) __nanosleep(200);
                    l2_prefetch(wo + (size_t)g * 2097152 + (size_t)p3_kblock(i) * 131072 + (bid & 31) * 4096, 4096);
                    next += PF_WO_INTERVAL;
                }
                TL(7);
            }
        } else {
            const int i6 = tid & 63;
            unsigned* aflag = g_aflag + (bid >> 2) * 32;
            unsigned* bflag = g_bflag + t * 32;
            if (i6 == 0) {
                const unsigned av = ld_relaxed(aflag), bv = ld_relaxed(bflag);
                asm volatile("st.shared.v2.u32 [%0], {%1, %2};" ::"r"(sb + OFF_ZT), "r"((av / A_CNT + 1) * A_CNT), "r"((bv / B_CNT + 1) * B_CNT) : "memory");
            }
            uint4* qz = g_qbuf + (size_t)((b * 4 + g) * 2 + r) * 3072 + s * 1536 + i6;
#pragma unroll 1
            for (int k = 0; k < 24; k++) { qz[k * 64] = make_uint4(0, 0, 0, 0); if (CLR_SLEEP) __nanosleep(CLR_SLEEP); }
            bar_sync_n(4, 64);
            if (i6 == 0) { red_release(aflag, 1); mbar_arrive(sb + OFF_BAR + (BAR_GO2 + 1) * 8); }
            mbar_wait(sb + OFF_BAR + BAR_GO2 * 8, 0);
            uint4* oz = g_obuf + (size_t)(g * 4 + t) * 12288 + col * 1536 + i6;
#pragma unroll 1
            for (int k = 0; k < 24; k++) { oz[k * 64] = make_uint4(0, 0, 0, 0); __nanosleep(100); }
#pragma unroll
            for (int k = 0; k < 6; k++) {
                const int e = i6 + k * 64;
                *((uint4*)(out + (size_t)(t * 96 + g * 24 + (e >> 4)) * 1024 + col * 128) + (e & 15)) = make_uint4(0, 0, 0, 0);
            }
            bar_sync_n(4, 64);
            if (i6 == 0) { red_release(bflag, 1); mbar_arrive(sb + OFF_BAR + (BAR_GO2 + 1) * 8); }
        }
        __syncwarp();
        asm volatile("barrier.cluster.wait.aligned;" ::: "memory");
        TL_DUMP();
    } else {
        asm volatile("setmaxnreg.inc.sync.aligned.u32 160;");
        const uint32_t qpiece = sb + OFF_Q + wg * 16384;
        const int mi = lane >> 3;
        if (wg > 0) {
            float acc[48];
            proj_mainloop<false>(acc, sb, wg - 1, lane);
            if (tid == 128) TL(8);
#pragma unroll
            for (int bb = 0; bb < 2; bb++)
#pragma unroll
                for (int v = 0; v < 3; v++) {
                    const int j = 6 * bb + 2 * v;
                    char* dst = (char*)g_qbuf + (size_t)(((2 * t + bb) * 4 + g) * 2 + r) * 49152 + ((3 * mem + v) * 8 + (wg - 1) * 4 + warp) * 512 + lane * 16;
                    st_relaxed_v4(dst, pack_nz(acc[4 * j], acc[4 * j + 1]), pack_nz(acc[4 * j + 2], acc[4 * j + 3]),
                                  pack_nz(acc[4 * j + 4], acc[4 * j + 5]), pack_nz(acc[4 * j + 6], acc[4 * j + 7]));
                }
            if (tid == 128) TL(9);
        } else {
            mbar_wait(sb + OFF_BAR + (BAR_GO2 + 3) * 8, 0);
        }
        if ((tid & 127) == 0) mbar_expect_tx(sb + OFF_BAR + (BAR_XFULL + wg) * 8, 128 * 9 * 16);
        const char* qsrc = (const char*)g_qbuf + (size_t)((b * 4 + g) * 2 + r) * 49152 + (4 * wg + warp) * 4096 + lane * 16;
        {
            uint4 v[8];
            bool ok;
            do {
                probe_wait(qsrc - lane * 16 + (lane & 7) * 512);
                if (lane == 0 && warp == 0) TL(42 + wg);
                ok = true;
#pragma unroll
                for (int i = 0; i < 8; i++) v[i] = ld_relaxed_v4(qsrc + i * 512);
#pragma unroll
                for (int i = 0; i < 8; i++) ok = ok && valid4(v[i]);
            } while (!__all_sync(0xffffffffu, ok));
            const uint32_t a0 = qpiece + (16 * warp + (mi >> 1) * 8 + (lane & 7)) * 128;
#pragma unroll
            for (int i = 0; i < 8; i++)
                stsm_x4_t(a0 + (i >> 2) * 8192 + (((2 * (i & 3) + (mi & 1)) ^ (lane & 7)) << 4), v[i].x, v[i].y, v[i].z, v[i].w);
            fence_async_smem();
            if (lane == 0) mbar_arrive(sb + OFF_BAR + (BAR_GO2 + 2) * 8);
            named_sync(1 + wg);
        }
        asm volatile("barrier.cluster.wait.aligned;" ::: "memory");

        {
            const float c = 0.08838834764831845f * 1.4426950408889634f;
            float o[64];
            float m0 = 0.f, m1 = 0.f, l0 = 0.f, l1 = 0.f;
            if (lane == 0 && warp == 0) TL(10 + wg);
            const uint64_t dq = mkdesc(qpiece, 0, 1024);
#pragma unroll 1
            for (int j = 0; j < 8; j++) {
                float sc[64];
                const uint32_t kslot = (0x03142031u >> (4 * j)) & 7, vslot = (0x14203142u >> (4 * j)) & 7;
                TLC(j * 6 + 0);
                mbar_wait(sb + OFF_BAR + (BAR_FULL + kslot) * 8, (0x63u >> j) & 1);
                TLC(j * 6 + 1);
                {
                    const uint64_t dk = mkdesc(sb + OFF_RING + kslot * SLOT, 0, 1024);
                    wg_fence();
#pragma unroll
                    for (int kk = 0; kk < 8; kk++)
                        wgmma_n128_ss<0, 0>(sc, dq + (kk >> 2) * (8192 >> 4) + (kk & 3) * 2, dk + (kk >> 2) * (16384 >> 4) + (kk & 3) * 2, kk != 0);
                    wg_commit();
                    wg_wait<0>();
                    reg_fence(sc);
                }
                TLC(j * 6 + 2);
                if (lane == 0) mbar_arrive(sb + OFF_BAR + (BAR_EMPTY + kslot) * 8);
                if (j == 0) {
                    float x0 = fmaxf(sc[0], sc[1]), x1 = fmaxf(sc[2], sc[3]), y0 = fmaxf(sc[4], sc[5]), y1 = fmaxf(sc[6], sc[7]);
#pragma unroll
                    for (int i = 8; i < 64; i += 8) {
                        x0 = fmaxf(x0, fmaxf(sc[i], sc[i + 1])); x1 = fmaxf(x1, fmaxf(sc[i + 2], sc[i + 3]));
                        y0 = fmaxf(y0, fmaxf(sc[i + 4], sc[i + 5])); y1 = fmaxf(y1, fmaxf(sc[i + 6], sc[i + 7]));
                    }
                    x0 = fmaxf(x0, y0); x1 = fmaxf(x1, y1);
                    x0 = fmaxf(x0, __shfl_xor_sync(0xffffffffu, x0, 1)); x1 = fmaxf(x1, __shfl_xor_sync(0xffffffffu, x1, 1));
                    x0 = fmaxf(x0, __shfl_xor_sync(0xffffffffu, x0, 2)); x1 = fmaxf(x1, __shfl_xor_sync(0xffffffffu, x1, 2));
                    m0 = x0 * c; m1 = x1 * c;
                }
                if (j == 7 && lane == 0) mbar_arrive_remote(mapa(sb + OFF_BAR + (BAR_XFREE + wg) * 8, s ^ 1));
                uint32_t p[32];
                TLC(j * 6 + 3);
                mbar_wait(sb + OFF_BAR + (BAR_FULL + vslot) * 8, (0x73u >> j) & 1);
                TLC(j * 6 + 4);
                const uint64_t dv = mkdesc(sb + OFF_RING + vslot * SLOT, 16384, 1024);
#pragma unroll
                for (int ch = 0; ch < 2; ch++) {
#pragma unroll
                    for (int i = ch * 8; i < ch * 8 + 8; i++) {
                        const float e0 = ex2(fmaf(sc[4 * i], c, -m0)), e1 = ex2(fmaf(sc[4 * i + 1], c, -m0));
                        const float e2 = ex2(fmaf(sc[4 * i + 2], c, -m1)), e3 = ex2(fmaf(sc[4 * i + 3], c, -m1));
                        p[2 * i] = pack_bf16(e0, e1);
                        p[2 * i + 1] = pack_bf16(e2, e3);
                    }
                    wg_fence();
#pragma unroll
                    for (int kk = ch * 4; kk < ch * 4 + 4; kk++)
                        wgmma_n128_rs<1>(o, p[4 * kk], p[4 * kk + 1], p[4 * kk + 2], p[4 * kk + 3], dv + kk * (2048 >> 4), (j | kk) != 0);
                    wg_commit();
                    const uint32_t* q = p + ch * 16;
                    const uint32_t a = hadd2(hadd2(hadd2(q[0], q[2]), hadd2(q[4], q[6])), hadd2(hadd2(q[8], q[10]), hadd2(q[12], q[14])));
                    const uint32_t d = hadd2(hadd2(hadd2(q[1], q[3]), hadd2(q[5], q[7])), hadd2(hadd2(q[9], q[11]), hadd2(q[13], q[15])));
                    l0 += __uint_as_float(a << 16) + __uint_as_float(a & 0xffff0000u);
                    l1 += __uint_as_float(d << 16) + __uint_as_float(d & 0xffff0000u);
                }
                wg_wait<0>();
                reg_fence(o);
                if (lane == 0) mbar_arrive(sb + OFF_BAR + (BAR_EMPTY + vslot) * 8);
                TLC(j * 6 + 5);
            }

            if (__any_sync(0xffffffffu, !(l0 <= L_SAFE && l1 <= L_SAFE))) {
                float fo[64], fml[4];
                const size_t kvoff = (size_t)((b * 4 + g) * 2048 + s * 1024) * 256;
                const char* qs = (const char*)g_qbuf + (size_t)((b * 4 + g) * 2 + r) * 49152 + (4 * wg + warp) * 4096 + (threadIdx.x & 31) * 16;
                attention_fallback(fo, fml, qs, kc + kvoff, vc + kvoff, c);
#pragma unroll
                for (int i = 0; i < 64; i++) o[i] = fo[i];
                m0 = fml[0]; m1 = fml[1]; l0 = fml[2]; l1 = fml[3];
            }
            l0 += __shfl_xor_sync(0xffffffffu, l0, 1); l1 += __shfl_xor_sync(0xffffffffu, l1, 1);
            l0 += __shfl_xor_sync(0xffffffffu, l0, 2); l1 += __shfl_xor_sync(0xffffffffu, l1, 2);
            const int u = 4 * wg + warp;
            char* odst = (char*)g_obuf + (size_t)((g * 4 + t) * 16 + (4 * r + u / 3) * 2 + s) * 12288 + ((b & 1) * 3 + u % 3) * 2048 + lane * 16;
            if (s == 0) combine_and_store<0>(o, m0, m1, l0, l1, sb, wg, warp, lane, tid, odst);
            else combine_and_store<1>(o, m0, m1, l0, l1, sb, wg, warp, lane, tid, odst);
            if (lane == 0 && warp == 0) TL(13 + wg);
        }

        if (wg == 0) {
            const char* osrc = (const char*)g_obuf + (size_t)(g * 4 + t) * 196608 + warp * 3072 + lane * 16;
            uint4 va[12], vb[12];
            auto load = [&](uint4 (&v)[12], int n) {
#pragma unroll
                for (int y = 0; y < 12; y++) v[y] = ld_relaxed_v4(osrc + p3_kblock(2 * n + y / 6) * 12288 + (y % 6) * 512);
            };
            auto finish = [&](uint4 (&v)[12], int n) {
                while (true) {
                    bool ok = true;
#pragma unroll
                    for (int y = 0; y < 12; y++) ok = ok && valid4(v[y]);
                    if (__all_sync(0xffffffffu, ok)) break;
                    probe_wait(osrc - lane * 16 + p3_kblock(2 * n + ((lane >> 1) & 1)) * 12288 + (lane & 1) * 5 * 512);
                    load(v, n);
                }
#pragma unroll
                for (int h = 0; h < 2; h++) {
                    const int f = 32 + 2 * n + h, slot = f % NSLOT;
                    mbar_wait(sb + OFF_BAR + (BAR_EMPTY + slot) * 8, ((f / NSLOT) & 1) ^ 1);
#pragma unroll
                    for (int y = 0; y < 6; y++) {
                        const int z = warp * 6 + y;
                        const uint32_t a = sb + OFF_RING + slot * SLOT + 16384 + ((z >> 2) * 16 + (mi & 1) * 8 + (lane & 7)) * 128 +
                                           (((2 * (z & 3) + (mi >> 1)) ^ (lane & 7)) << 4);
                        stsm_x4(a, v[6 * h + y].x, v[6 * h + y].y, v[6 * h + y].z, v[6 * h + y].w);
                    }
                    fence_async_smem();
                    __syncwarp();
                    if (lane == 0) mbar_arrive(sb + OFF_BAR + (BAR_OFULL + slot) * 8);
                }
                if (n == 0 && tid == 0) TL(4);
                if (n == 7 && tid == 0) TL(5);
            };
            probe_wait(osrc - lane * 16 + p3_kblock((lane >> 1) & 1) * 12288 + (lane & 1) * 5 * 512);
            load(va, 0);
#pragma unroll
            for (int n = 0; n < 8; n += 2) {
                load(vb, n + 1);
                finish(va, n);
                if (n + 2 < 8) load(va, n + 2);
                finish(vb, n + 1);
            }
        } else {
            float acc[48];
            proj_mainloop<true>(acc, sb, wg - 1, lane);
            if (tid == 128) TL(40);
            named_sync(1 + wg);
            const uint32_t a0 = qpiece + ((mi >> 1) * 8 + (lane & 7)) * 128 + (((2 * warp + (mi & 1)) ^ (lane & 7)) << 4);
#pragma unroll
            for (int j = 0; j < 12; j += 2)
                stsm_x4_t(a0 + j * 1024, pack_bf16(acc[4 * j], acc[4 * j + 1]), pack_bf16(acc[4 * j + 2], acc[4 * j + 3]),
                          pack_bf16(acc[4 * j + 4], acc[4 * j + 5]), pack_bf16(acc[4 * j + 6], acc[4 * j + 7]));
            fence_async_smem();
            named_sync(1 + wg);
            if (warp == 0 && elect_one()) {
                tma_reduce_add_2d(&tm_out, col * 128 + (wg - 1) * 64, t * 96, qpiece);
                bulk_commit();
                bulk_wait0_read();
                if (wg == 1) TL(41);
            }
            __syncwarp();
        }
        TL_DUMP();
    }
}

typedef CUresult (*EncodeFn)(CUtensorMap*, CUtensorMapDataType, cuuint32_t, void*, const cuuint64_t*, const cuuint64_t*,
                             const cuuint32_t*, const cuuint32_t*, CUtensorMapInterleave, CUtensorMapSwizzle,
                             CUtensorMapL2promotion, CUtensorMapFloatOOBfill);

void make_map(EncodeFn enc, CUtensorMap* m, const void* ptr, int rank, uint64_t rows, uint64_t cols, uint32_t box_rows) {
    cuuint64_t dims[3] = {rank == 2 ? cols : 64, rows, cols / 64};
    cuuint64_t strides[2] = {cols * 2, 128};
    cuuint32_t box[3] = {64, box_rows, 2};
    cuuint32_t es[3] = {1, 1, 1};
    enc(m, CU_TENSOR_MAP_DATA_TYPE_BFLOAT16, rank, const_cast<void*>(ptr), dims, strides, box, es, CU_TENSOR_MAP_INTERLEAVE_NONE,
        CU_TENSOR_MAP_SWIZZLE_128B, CU_TENSOR_MAP_L2_PROMOTION_L2_256B, CU_TENSOR_MAP_FLOAT_OOB_FILL_NONE);
}

}

extern "C" void kernel_launch(void* const* d_in, const int* in_sizes, int n_in, void* d_out, int out_size) {
    (void)in_sizes; (void)n_in; (void)out_size;
    static EncodeFn enc = nullptr;
    if (!enc) {
        void* fn = nullptr;
        cudaDriverEntryPointQueryResult qr;
        cudaGetDriverEntryPoint("cuTensorMapEncodeTiled", &fn, cudaEnableDefault, &qr);
        enc = (EncodeFn)fn;
        cudaFuncSetAttribute(gqa_fused_kernel, cudaFuncAttributeMaxDynamicSharedMemorySize, SMEM_TOTAL);
    }
    CUtensorMap tx, twq, tk, tv, two, tout;
    make_map(enc, &tx, d_in[0], 2, 384, 1024, 48);
    make_map(enc, &tk, d_in[1], 3, 65536, 128, 128);
    make_map(enc, &tv, d_in[2], 2, 65536, 128, 128);
    {
        cuuint64_t dims[4] = {64, 1024, 2, 32};
        cuuint64_t strides[3] = {8192, 128, 256};
        cuuint32_t box[4] = {64, 64, 1, 4};
        cuuint32_t es[4] = {1, 1, 1, 1};
        enc(&twq, CU_TENSOR_MAP_DATA_TYPE_BFLOAT16, 4, d_in[3], dims, strides, box, es, CU_TENSOR_MAP_INTERLEAVE_NONE,
            CU_TENSOR_MAP_SWIZZLE_128B, CU_TENSOR_MAP_L2_PROMOTION_L2_256B, CU_TENSOR_MAP_FLOAT_OOB_FILL_NONE);
    }
    make_map(enc, &two, d_in[4], 3, 4096, 1024, 64);
    make_map(enc, &tout, d_out, 2, 384, 1024, 48);
    gqa_fused_kernel<<<NCTA + 4, NTHREADS, SMEM_TOTAL, cudaStreamPerThread>>>(tx, twq, tk, tv, two, tout, (__nv_bfloat16*)d_out,
        (const char*)d_in[0], (const char*)d_in[3], (const char*)d_in[1], (const char*)d_in[2], (const char*)d_in[4]);
}
```

```cpp
#include <cuda_runtime.h>
#include <cuda_bf16.h>
#include <cuda.h>
#include <stdint.h>

namespace {

constexpr int NCTA = 128;
constexpr int NTHREADS = 512;
constexpr int SLOT = 32768;
constexpr int NSLOT = 5;
constexpr int OFF_ZERO = 0;
constexpr int OFF_Q = 8192;
constexpr int OFF_ML = OFF_Q + 49152;
constexpr int OFF_RING = OFF_ML + 6144;
constexpr int OFF_BAR = OFF_RING + NSLOT * SLOT;
constexpr int SMEM_BYTES = OFF_BAR + 576;
constexpr int NS1 = 6, OFF_X1 = 38912;
constexpr int NW3 = 9, NO3 = 6;
constexpr int BAR_FULL = 0, BAR_EMPTY = 5,
              BAR_FULL1 = 10, BAR_EMPTY1 = 16, BAR_EMPTY3 = 22,
              BAR_XFREE = 28, BAR_CDONE = 31,
              BAR_GO2 = 34,
              BAR_ONES = 35, BAR_XFULL = 35, BAR_XML = 38, BAR_QFULL = 41, BAR_QFREE = 44, BAR_BOK = 46, BAR_GRP = 47,
              BAR_FULL3 = 49, BAR_OFULL = 55, BAR_WFULL = 61, BAR_END = 70;

constexpr unsigned B_CNT = 64;
#define PLACE 1
#define SCHED 3
#define ARR_CH 1
#define NCHK 2
#define CHB 0x850
#define WSTEP 2
#define GO2_AT 9
#define CLR_GAP 500
#define H_SEQ 0x765410
#define H_KV_N 6
#define H_START 2000
#define H_KV_INT 500
#define H_WO_START 26000
#define H_WO_INT 500
#define RMAP 0
#define H_W0 16
#define H_WSTART 1000
#define H_WINT 0
#define H_X 1
#define KV_GAP 600
#define PRE_GAP 0
#define H_XSTART 0
#define SKEW3 0
constexpr int SPIN_LIMIT = 1 << 22;
constexpr float SCALE_LOG2E = 0.08838834764831845f * 1.4426950408889634f;
constexpr float L_SAFE = 1.0995116e12f;

__device__ uint4 g_oimg[16 * 16 * 12288 / 16];
__device__ unsigned g_bflag[2 * 32];

__device__ __forceinline__ void TL(int) {}
__device__ __forceinline__ void TLP(int, uint32_t, int) {}
#define TLC(idx)
#define TLF(idx)
#define TLPF(c, sb, idx)
#define STALL_BEGIN()
#define STALL_END(idx)
#define TL_INIT()
#define TL_DUMP()
#define TL_DONE()
constexpr int SMEM_TOTAL = SMEM_BYTES;

__device__ __forceinline__ uint32_t smem_u32(const void* p) { return (uint32_t)__cvta_generic_to_shared(p); }
__device__ __forceinline__ void mbar_init(uint32_t bar, uint32_t cnt) {
    asm volatile("mbarrier.init.shared::cta.b64 [%0], %1;" ::"r"(bar), "r"(cnt) : "memory");
}
__device__ __forceinline__ void mbar_expect_tx(uint32_t bar, uint32_t bytes) {
    asm volatile("mbarrier.arrive.expect_tx.shared::cta.b64 _, [%0], %1;" ::"r"(bar), "r"(bytes) : "memory");
}
__device__ __forceinline__ void mbar_arrive(uint32_t bar) {
    asm volatile("mbarrier.arrive.shared::cta.b64 _, [%0];" ::"r"(bar) : "memory");
}
__device__ __forceinline__ void mbar_arrive_cnt(uint32_t bar, uint32_t cnt) {
    asm volatile("mbarrier.arrive.shared::cta.b64 _, [%0], %1;" ::"r"(bar), "r"(cnt) : "memory");
}
__device__ __forceinline__ void mbar_arrive_remote(uint32_t cluster_addr) {
    asm volatile("fence.release.sync_restrict::shared::cta.cluster;\n"
                 "mbarrier.arrive.relaxed.cluster.shared::cluster.b64 _, [%0];" ::"r"(cluster_addr) : "memory");
}
#define SPIN_GUARD(it) asm volatile("{\n.reg .pred q;\nsetp.gt.s32 q, %0, %1;\n@q trap;\n}" ::"r"(it), "n"(SPIN_LIMIT));
__device__ __forceinline__ void (mbar_wait)(uint32_t bar, uint32_t parity) {
    asm volatile(
        "{\n.reg .pred p, q;\n.reg .u32 c;\nmov.u32 c, 0;\n"
        "WAIT_LOOP:\n"
        "mbarrier.try_wait.parity.shared::cta.b64 p, [%0], %1;\n"
        "@p bra WAIT_DONE;\n"
        "add.u32 c, c, 1;\nsetp.gt.u32 q, c, %2;\n@q trap;\n"
        "bra WAIT_LOOP;\n"
        "WAIT_DONE:\n}\n" ::"r"(bar), "r"(parity), "n"(SPIN_LIMIT) : "memory");
}
__device__ __forceinline__ void (mbar_wait_cluster)(uint32_t bar, uint32_t parity) {
    asm volatile(
        "{\n.reg .pred p, q;\n.reg .u32 c;\nmov.u32 c, 0;\n"
        "WAIT_LOOP:\n"
        "mbarrier.try_wait.parity.acquire.cluster.shared::cta.b64 p, [%0], %1;\n"
        "@p bra WAIT_DONE;\n"
        "add.u32 c, c, 1;\nsetp.gt.u32 q, c, %2;\n@q trap;\n"
        "bra WAIT_LOOP;\n"
        "WAIT_DONE:\n}\n" ::"r"(bar), "r"(parity), "n"(SPIN_LIMIT) : "memory");
}
__device__ __forceinline__ bool elect_one() {
    uint32_t el;
    asm volatile("{\n.reg .pred p;\nelect.sync _|p, 0xffffffff;\nselp.u32 %0, 1, 0, p;\n}" : "=r"(el));
    return el != 0;
}
__device__ __forceinline__ void prefetch_tmap(const CUtensorMap* tm) { asm volatile("prefetch.tensormap [%0];" ::"l"(tm) : "memory"); }
__device__ __forceinline__ uint32_t mapa(uint32_t addr, uint32_t rank) {
    uint32_t r;
    asm("mapa.shared::cluster.u32 %0, %1, %2;" : "=r"(r) : "r"(addr), "r"(rank));
    return r;
}
__device__ __forceinline__ void tma_2d(uint32_t dst, const CUtensorMap* tm, int c0, int c1, uint32_t bar) {
    asm volatile("cp.async.bulk.tensor.2d.shared::cluster.global.mbarrier::complete_tx::bytes [%0], [%1, {%3, %4}], [%2];"
                 ::"r"(dst), "l"(tm), "r"(bar), "r"(c0), "r"(c1) : "memory");
}
__device__ __forceinline__ void tma_3d(uint32_t dst, const CUtensorMap* tm, int c0, int c1, int c2, uint32_t bar) {
    asm volatile("cp.async.bulk.tensor.3d.shared::cluster.global.mbarrier::complete_tx::bytes [%0], [%1, {%3, %4, %5}], [%2];"
                 ::"r"(dst), "l"(tm), "r"(bar), "r"(c0), "r"(c1), "r"(c2) : "memory");
}
__device__ __forceinline__ void tma_4d(uint32_t dst, const CUtensorMap* tm, int c0, int c1, int c2, int c3, uint32_t bar) {
    asm volatile("cp.async.bulk.tensor.4d.shared::cluster.global.mbarrier::complete_tx::bytes [%0], [%1, {%3, %4, %5, %6}], [%2];"
                 ::"r"(dst), "l"(tm), "r"(bar), "r"(c0), "r"(c1), "r"(c2), "r"(c3) : "memory");
}
__device__ __forceinline__ void bulk_s2peer(uint32_t dst_cluster, uint32_t src, uint32_t bytes, uint32_t bar_cluster) {
    asm volatile("cp.async.bulk.shared::cluster.shared::cta.mbarrier::complete_tx::bytes [%0], [%1], %2, [%3];"
                 ::"r"(dst_cluster), "r"(src), "r"(bytes), "r"(bar_cluster) : "memory");
}
__device__ __forceinline__ void bulk_g2s(uint32_t dst, const void* src, uint32_t bytes, uint32_t bar) {
    asm volatile("cp.async.bulk.shared::cluster.global.mbarrier::complete_tx::bytes [%0], [%1], %2, [%3];"
                 ::"r"(dst), "l"(src), "r"(bytes), "r"(bar) : "memory");
}
__device__ __forceinline__ void bulk_s2g(void* dst, uint32_t src, uint32_t bytes) {
    asm volatile("cp.async.bulk.global.shared::cta.bulk_group [%0], [%1], %2;" ::"l"(dst), "r"(src), "r"(bytes) : "memory");
}
__device__ __forceinline__ void tma_reduce_add_2d(const CUtensorMap* tm, int c0, int c1, uint32_t src) {
    asm volatile("cp.reduce.async.bulk.tensor.2d.global.shared::cta.add.tile.bulk_group [%0, {%2, %3}], [%1];"
                 ::"l"(tm), "r"(src), "r"(c0), "r"(c1) : "memory");
}
__device__ __forceinline__ void l2_prefetch(const void* src, uint32_t bytes) {
    asm volatile("cp.async.bulk.prefetch.L2.global [%0], %1;" ::"l"(src), "r"(bytes) : "memory");
}
__device__ __forceinline__ uint32_t clock32() {
    uint32_t c;
    asm volatile("mov.u32 %0, %%clock;" : "=r"(c)::"memory");
    return c;
}
__device__ __forceinline__ void bulk_commit() { asm volatile("cp.async.bulk.commit_group;" ::: "memory"); }
__device__ __forceinline__ void bulk_wait0() { asm volatile("cp.async.bulk.wait_group 0;" ::: "memory"); }
__device__ __forceinline__ void bulk_wait0_read() { asm volatile("cp.async.bulk.wait_group.read 0;" ::: "memory"); }
__device__ __forceinline__ void fence_async_smem() { asm volatile("fence.proxy.async.shared::cta;" ::: "memory"); }
__device__ __forceinline__ void fence_async_all() { asm volatile("fence.proxy.async;" ::: "memory"); }
__device__ __forceinline__ void red_release(unsigned* p, unsigned v) {
    asm volatile("red.release.gpu.global.add.u32 [%0], %1;" ::"l"(p), "r"(v) : "memory");
}
__device__ __forceinline__ unsigned ld_acquire(const unsigned* p) {
    unsigned v;
    asm volatile("ld.acquire.gpu.global.u32 %0, [%1];" : "=r"(v) : "l"(p) : "memory");
    return v;
}
__device__ __forceinline__ unsigned ld_relaxed(const unsigned* p) {
    unsigned v;
    asm volatile("ld.relaxed.gpu.global.u32 %0, [%1];" : "=r"(v) : "l"(p) : "memory");
    return v;
}
__device__ __forceinline__ void (flag_wait)(const unsigned* p, unsigned target) {
    asm volatile(
        "{\n.reg .pred p, q;\n.reg .u32 c, v;\nmov.u32 c, 0;\n"
        "FLAG_LOOP:\n"
        "ld.acquire.gpu.global.u32 v, [%0];\n"
        "sub.u32 v, v, %1;\nsetp.ge.s32 p, v, 0;\n"
        "@p bra FLAG_DONE;\n"
        "add.u32 c, c, 1;\nsetp.gt.u32 q, c, %2;\n@q trap;\n"
        "bra FLAG_LOOP;\n"
        "FLAG_DONE:\n}\n" ::"l"(p), "r"(target), "n"(SPIN_LIMIT) : "memory");
}
__device__ __forceinline__ void named_sync(int id) { asm volatile("bar.sync %0, 128;" ::"r"(id) : "memory"); }
__device__ __forceinline__ void wg_fence() { asm volatile("wgmma.fence.sync.aligned;" ::: "memory"); }
__device__ __forceinline__ void wg_commit() { asm volatile("wgmma.commit_group.sync.aligned;" ::: "memory"); }
template <int N> __device__ __forceinline__ void wg_wait() { asm volatile("wgmma.wait_group.sync.aligned %0;" ::"n"(N) : "memory"); }
template <int N> __device__ __forceinline__ void reg_fence(float (&d)[N]) {
#pragma unroll
    for (int i = 0; i < N; i++) asm volatile("" : "+f"(d[i])::"memory");
}
__device__ __forceinline__ uint64_t mkdesc(uint32_t addr, uint32_t lbo, uint32_t sbo) {
    return (uint64_t)((addr & 0x3FFFF) >> 4) | ((uint64_t)(lbo >> 4) << 16) | ((uint64_t)(sbo >> 4) << 32) | (1ull << 62);
}
__device__ __forceinline__ uint32_t pack_bf16(float lo, float hi) {
    uint32_t r;
    asm("cvt.rn.bf16x2.f32 %0, %1, %2;" : "=r"(r) : "f"(hi), "f"(lo));
    return r;
}
__device__ __forceinline__ uint32_t hadd2(uint32_t a, uint32_t b) {
    uint32_t r;
    asm("add.rn.bf16x2 %0, %1, %2;" : "=r"(r) : "r"(a), "r"(b));
    return r;
}
__device__ __forceinline__ float ex2(float x) {
    float y;
    asm("ex2.approx.ftz.f32 %0, %1;" : "=f"(y) : "f"(x));
    return y;
}
__device__ __forceinline__ void stsm_x4(uint32_t addr, uint32_t r0, uint32_t r1, uint32_t r2, uint32_t r3) {
    asm volatile("stmatrix.sync.aligned.m8n8.x4.shared.b16 [%0], {%1, %2, %3, %4};" ::"r"(addr), "r"(r0), "r"(r1), "r"(r2), "r"(r3) : "memory");
}
__device__ __forceinline__ void stsm_x4_t(uint32_t addr, uint32_t r0, uint32_t r1, uint32_t r2, uint32_t r3) {
    asm volatile("stmatrix.sync.aligned.m8n8.x4.trans.shared.b16 [%0], {%1, %2, %3, %4};" ::"r"(addr), "r"(r0), "r"(r1), "r"(r2), "r"(r3) : "memory");
}
__device__ __forceinline__ void st_async_v4(uint32_t addr, float a, float b, float c, float d, uint32_t bar) {
    asm volatile("st.async.weak.shared::cluster.mbarrier::complete_tx::bytes.v4.f32 [%0], {%1, %2, %3, %4}, [%5];"
                 ::"r"(addr), "f"(a), "f"(b), "f"(c), "f"(d), "r"(bar) : "memory");
}
__device__ __forceinline__ void st_async_v4u(uint32_t addr, uint32_t a, uint32_t b, uint32_t c, uint32_t d, uint32_t bar) {
    asm volatile("st.async.weak.shared::cluster.mbarrier::complete_tx::bytes.v4.b32 [%0], {%1, %2, %3, %4}, [%5];"
                 ::"r"(addr), "r"(a), "r"(b), "r"(c), "r"(d), "r"(bar) : "memory");
}
__device__ __forceinline__ uint32_t lds_u32(uint32_t addr) {
    uint32_t v;
    asm volatile("ld.shared.u32 %0, [%1];" : "=r"(v) : "r"(addr) : "memory");
    return v;
}
__device__ __forceinline__ float rcp_fast(float x) {
    float y;
    asm("rcp.approx.ftz.f32 %0, %1;" : "=f"(y) : "f"(x));
    return y;
}
__device__ __forceinline__ float bf_lo(uint32_t w) { return __uint_as_float(w << 16); }
__device__ __forceinline__ float bf_hi(uint32_t w) { return __uint_as_float(w & 0xffff0000u); }
__device__ __forceinline__ float4 lds_v4(uint32_t addr) {
    float4 v;
    asm volatile("ld.shared.v4.f32 {%0, %1, %2, %3}, [%4];" : "=f"(v.x), "=f"(v.y), "=f"(v.z), "=f"(v.w) : "r"(addr) : "memory");
    return v;
}

__device__ __forceinline__ uint4 ld_relaxed_v4(const void* p) {
    uint4 v;
    asm volatile("ld.relaxed.gpu.global.v4.u32 {%0, %1, %2, %3}, [%4];" : "=r"(v.x), "=r"(v.y), "=r"(v.z), "=r"(v.w) : "l"(p) : "memory");
    return v;
}
__device__ __forceinline__ void st_relaxed_v4(void* p, uint32_t a, uint32_t b, uint32_t c, uint32_t d) {
    asm volatile("st.relaxed.gpu.global.v4.u32 [%0], {%1, %2, %3, %4};" ::"l"(p), "r"(a), "r"(b), "r"(c), "r"(d) : "memory");
}
__device__ __forceinline__ uint32_t pack_nz(float lo, float hi) {
    const uint32_t w = pack_bf16(lo, hi);
    return w == 0u ? 0x80008000u : w;
}
__device__ __forceinline__ bool valid4(const uint4& v) { return min(min(v.x, v.y), min(v.z, v.w)) != 0u; }
__device__ __forceinline__ void (probe_wait)(const void* p) {
    asm volatile(
        "{\n.reg .pred p, q;\n.reg .u32 c, v;\nmov.u32 c, 0;\n"
        "PROBE_LOOP:\n"
        "ld.relaxed.gpu.global.u32 v, [%0];\n"
        "setp.ne.u32 p, v, 0;\n"
        "vote.sync.all.pred p, p, 0xffffffff;\n"
        "@p bra PROBE_DONE;\n"
        "add.u32 c, c, 1;\nsetp.gt.u32 q, c, %1;\n@q trap;\n"
        "bra PROBE_LOOP;\n"
        "PROBE_DONE:\n}\n" ::"l"(p), "n"(SPIN_LIMIT) : "memory");
}
__device__ __forceinline__ void bar_sync_n(int id, int n) { asm volatile("bar.sync %0, %1;" ::"r"(id), "r"(n) : "memory"); }
__device__ __forceinline__ void bar_arrive_n(int id, int n) { asm volatile("bar.arrive %0, %1;" ::"r"(id), "r"(n) : "memory"); }
__device__ __forceinline__ uint32_t movm_t(uint32_t a) {
    uint32_t d;
    asm volatile("movmatrix.sync.aligned.m8n8.trans.b16 %0, %1;" : "=r"(d) : "r"(a));
    return d;
}
__device__ __forceinline__ void mma_16816(float* d, uint32_t a0, uint32_t a1, uint32_t a2, uint32_t a3, uint32_t b0, uint32_t b1) {
    asm volatile("mma.sync.aligned.m16n8k16.row.col.f32.bf16.bf16.f32 {%0, %1, %2, %3}, {%4, %5, %6, %7}, {%8, %9}, {%0, %1, %2, %3};"
                 : "+f"(d[0]), "+f"(d[1]), "+f"(d[2]), "+f"(d[3]) : "r"(a0), "r"(a1), "r"(a2), "r"(a3), "r"(b0), "r"(b1));
}

template <int V> struct Int { static constexpr int value = V; };

template <int TA, int TB>
__device__ __forceinline__ void wgmma_n48_ss(float (&d)[24], uint64_t da, uint64_t db, int scale_d) {
    asm volatile("{\n.reg .pred p;\nsetp.ne.b32 p, %26, 0;\n"
        "wgmma.mma_async.sync.aligned.m64n48k16.f32.bf16.bf16 {"
        "%0, %1, %2, %3, %4, %5, %6, %7, %8, %9, %10, %11, %12, %13, %14, %15, "
        "%16, %17, %18, %19, %20, %21, %22, %23}, "
        "%24, %25, p, 1, 1, %27, %28;\n}\n"
        : "+f"(d[0]), "+f"(d[1]), "+f"(d[2]), "+f"(d[3]), "+f"(d[4]), "+f"(d[5]), "+f"(d[6]), "+f"(d[7]),
          "+f"(d[8]), "+f"(d[9]), "+f"(d[10]), "+f"(d[11]), "+f"(d[12]), "+f"(d[13]), "+f"(d[14]), "+f"(d[15]),
          "+f"(d[16]), "+f"(d[17]), "+f"(d[18]), "+f"(d[19]), "+f"(d[20]), "+f"(d[21]), "+f"(d[22]), "+f"(d[23])
        : "l"(da), "l"(db), "r"(scale_d), "n"(TA), "n"(TB));
}
template <int TA, int TB>
__device__ __forceinline__ void wgmma_n96_ss(float (&d)[48], uint64_t da, uint64_t db, int scale_d) {
    asm volatile("{\n.reg .pred p;\nsetp.ne.b32 p, %50, 0;\n"
        "wgmma.mma_async.sync.aligned.m64n96k16.f32.bf16.bf16 {"
        "%0, %1, %2, %3, %4, %5, %6, %7, %8, %9, %10, %11, %12, %13, %14, %15, "
        "%16, %17, %18, %19, %20, %21, %22, %23, %24, %25, %26, %27, %28, %29, %30, %31, "
        "%32, %33, %34, %35, %36, %37, %38, %39, %40, %41, %42, %43, %44, %45, %46, %47}, "
        "%48, %49, p, 1, 1, %51, %52;\n}\n"
        : "+f"(d[0]), "+f"(d[1]), "+f"(d[2]), "+f"(d[3]), "+f"(d[4]), "+f"(d[5]), "+f"(d[6]), "+f"(d[7]),
          "+f"(d[8]), "+f"(d[9]), "+f"(d[10]), "+f"(d[11]), "+f"(d[12]), "+f"(d[13]), "+f"(d[14]), "+f"(d[15]),
          "+f"(d[16]), "+f"(d[17]), "+f"(d[18]), "+f"(d[19]), "+f"(d[20]), "+f"(d[21]), "+f"(d[22]), "+f"(d[23]),
          "+f"(d[24]), "+f"(d[25]), "+f"(d[26]), "+f"(d[27]), "+f"(d[28]), "+f"(d[29]), "+f"(d[30]), "+f"(d[31]),
          "+f"(d[32]), "+f"(d[33]), "+f"(d[34]), "+f"(d[35]), "+f"(d[36]), "+f"(d[37]), "+f"(d[38]), "+f"(d[39]),
          "+f"(d[40]), "+f"(d[41]), "+f"(d[42]), "+f"(d[43]), "+f"(d[44]), "+f"(d[45]), "+f"(d[46]), "+f"(d[47])
        : "l"(da), "l"(db), "r"(scale_d), "n"(TA), "n"(TB));
}
template <int TA, int TB>
__device__ __forceinline__ void wgmma_n128_ss(float (&d)[64], uint64_t da, uint64_t db, int scale_d) {
    asm volatile("{\n.reg .pred p;\nsetp.ne.b32 p, %66, 0;\n"
        "wgmma.mma_async.sync.aligned.m64n128k16.f32.bf16.bf16 {"
        "%0, %1, %2, %3, %4, %5, %6, %7, %8, %9, %10, %11, %12, %13, %14, %15, "
        "%16, %17, %18, %19, %20, %21, %22, %23, %24, %25, %26, %27, %28, %29, %30, %31, "
        "%32, %33, %34, %35, %36, %37, %38, %39, %40, %41, %42, %43, %44, %45, %46, %47, "
        "%48, %49, %50, %51, %52, %53, %54, %55, %56, %57, %58, %59, %60, %61, %62, %63}, "
        "%64, %65, p, 1, 1, %67, %68;\n}\n"
        : "+f"(d[0]), "+f"(d[1]), "+f"(d[2]), "+f"(d[3]), "+f"(d[4]), "+f"(d[5]), "+f"(d[6]), "+f"(d[7]),
          "+f"(d[8]), "+f"(d[9]), "+f"(d[10]), "+f"(d[11]), "+f"(d[12]), "+f"(d[13]), "+f"(d[14]), "+f"(d[15]),
          "+f"(d[16]), "+f"(d[17]), "+f"(d[18]), "+f"(d[19]), "+f"(d[20]), "+f"(d[21]), "+f"(d[22]), "+f"(d[23]),
          "+f"(d[24]), "+f"(d[25]), "+f"(d[26]), "+f"(d[27]), "+f"(d[28]), "+f"(d[29]), "+f"(d[30]), "+f"(d[31]),
          "+f"(d[32]), "+f"(d[33]), "+f"(d[34]), "+f"(d[35]), "+f"(d[36]), "+f"(d[37]), "+f"(d[38]), "+f"(d[39]),
          "+f"(d[40]), "+f"(d[41]), "+f"(d[42]), "+f"(d[43]), "+f"(d[44]), "+f"(d[45]), "+f"(d[46]), "+f"(d[47]),
          "+f"(d[48]), "+f"(d[49]), "+f"(d[50]), "+f"(d[51]), "+f"(d[52]), "+f"(d[53]), "+f"(d[54]), "+f"(d[55]),
          "+f"(d[56]), "+f"(d[57]), "+f"(d[58]), "+f"(d[59]), "+f"(d[60]), "+f"(d[61]), "+f"(d[62]), "+f"(d[63])
        : "l"(da), "l"(db), "r"(scale_d), "n"(TA), "n"(TB));
}
template <int TB>
__device__ __forceinline__ void wgmma_n128_rs(float (&d)[64], uint32_t a0, uint32_t a1, uint32_t a2, uint32_t a3, uint64_t db, int scale_d) {
    asm volatile("{\n.reg .pred p;\nsetp.ne.b32 p, %69, 0;\n"
        "wgmma.mma_async.sync.aligned.m64n128k16.f32.bf16.bf16 {"
        "%0, %1, %2, %3, %4, %5, %6, %7, %8, %9, %10, %11, %12, %13, %14, %15, "
        "%16, %17, %18, %19, %20, %21, %22, %23, %24, %25, %26, %27, %28, %29, %30, %31, "
        "%32, %33, %34, %35, %36, %37, %38, %39, %40, %41, %42, %43, %44, %45, %46, %47, "
        "%48, %49, %50, %51, %52, %53, %54, %55, %56, %57, %58, %59, %60, %61, %62, %63}, "
        "{%64, %65, %66, %67}, %68, p, 1, 1, %70;\n}\n"
        : "+f"(d[0]), "+f"(d[1]), "+f"(d[2]), "+f"(d[3]), "+f"(d[4]), "+f"(d[5]), "+f"(d[6]), "+f"(d[7]),
          "+f"(d[8]), "+f"(d[9]), "+f"(d[10]), "+f"(d[11]), "+f"(d[12]), "+f"(d[13]), "+f"(d[14]), "+f"(d[15]),
          "+f"(d[16]), "+f"(d[17]), "+f"(d[18]), "+f"(d[19]), "+f"(d[20]), "+f"(d[21]), "+f"(d[22]), "+f"(d[23]),
          "+f"(d[24]), "+f"(d[25]), "+f"(d[26]), "+f"(d[27]), "+f"(d[28]), "+f"(d[29]), "+f"(d[30]), "+f"(d[31]),
          "+f"(d[32]), "+f"(d[33]), "+f"(d[34]), "+f"(d[35]), "+f"(d[36]), "+f"(d[37]), "+f"(d[38]), "+f"(d[39]),
          "+f"(d[40]), "+f"(d[41]), "+f"(d[42]), "+f"(d[43]), "+f"(d[44]), "+f"(d[45]), "+f"(d[46]), "+f"(d[47]),
          "+f"(d[48]), "+f"(d[49]), "+f"(d[50]), "+f"(d[51]), "+f"(d[52]), "+f"(d[53]), "+f"(d[54]), "+f"(d[55]),
          "+f"(d[56]), "+f"(d[57]), "+f"(d[58]), "+f"(d[59]), "+f"(d[60]), "+f"(d[61]), "+f"(d[62]), "+f"(d[63])
        : "r"(a0), "r"(a1), "r"(a2), "r"(a3), "l"(db), "r"(scale_d), "n"(TB));
}

template <bool P3>
__device__ __forceinline__ void proj_mainloop(float (&acc)[48], uint32_t sb, int half, int lane) {
    constexpr int F0 = P3 ? 32 : 0;
    int slot = F0 % NSLOT, par = (F0 / NSLOT) & 1, opar = 0;
    int prev = 0;
#pragma unroll 1
    for (int kb = 0; kb < 16; kb++) {
        mbar_wait(sb + OFF_BAR + (BAR_FULL + slot) * 8, par);
        if (P3) mbar_wait(sb + OFF_BAR + (BAR_OFULL + slot) * 8, opar);
        const uint32_t st = __shfl_sync(0xffffffffu, sb + OFF_RING + slot * SLOT, 0);
        const uint64_t da = mkdesc(st + half * 8192, 0, 1024);
        const uint64_t db = mkdesc(st + 16384, 0, 1024);
        wg_fence();
#pragma unroll
        for (int kk = 0; kk < 4; kk++) wgmma_n96_ss<1, 0>(acc, da + kk * (2048 >> 4), db + kk * (32 >> 4), (kb | kk) != 0);
        wg_commit();
        if (threadIdx.x == 128 && (kb & 1) == 0) TL((P3 ? 56 : 48) + kb / 2);
        if (kb > 0) {
            wg_wait<1>();
            if (lane == 0) mbar_arrive_cnt(sb + OFF_BAR + (BAR_EMPTY + prev) * 8, 2 - half);
        }
        prev = slot;
        if (++slot == NSLOT) { slot = 0; par ^= 1; }
        if (slot == F0 % NSLOT) opar ^= 1;
    }
    wg_wait<0>();
    reg_fence(acc);
    if (lane == 0) mbar_arrive_cnt(sb + OFF_BAR + (BAR_EMPTY + prev) * 8, 2 - half);
}

__device__ __noinline__ void attention_fallback(float* o, float* ml, const char* qsrc, const char* kptr, const char* vptr, float c) {
    const int lane = threadIdx.x & 31;
    uint32_t q[32];
#pragma unroll
    for (int i = 0; i < 8; i++) {
        const uint4 v = ld_relaxed_v4(qsrc + i * 512);
        q[4 * i] = movm_t(v.x); q[4 * i + 2] = movm_t(v.y); q[4 * i + 1] = movm_t(v.z); q[4 * i + 3] = movm_t(v.w);
    }
    float acc[64];
#pragma unroll
    for (int i = 0; i < 64; i++) acc[i] = 0.f;
    float m0 = -INFINITY, m1 = -INFINITY, l0 = 0.f, l1 = 0.f;
#pragma unroll 1
    for (int k0 = 0; k0 < 1024; k0 += 16) {
        float sc[8];
#pragma unroll
        for (int i = 0; i < 8; i++) sc[i] = 0.f;
#pragma unroll
        for (int nb = 0; nb < 2; nb++)
#pragma unroll
            for (int kk = 0; kk < 8; kk++) {
                const char* kp = kptr + (size_t)(k0 + nb * 8 + (lane >> 2)) * 256 + kk * 32 + (lane & 3) * 4;
                mma_16816(sc + 4 * nb, q[4 * kk], q[4 * kk + 1], q[4 * kk + 2], q[4 * kk + 3], *(const uint32_t*)kp, *(const uint32_t*)(kp + 16));
            }
        float n0 = fmaxf(fmaxf(sc[0], sc[1]), fmaxf(sc[4], sc[5])) * c, n1 = fmaxf(fmaxf(sc[2], sc[3]), fmaxf(sc[6], sc[7])) * c;
        n0 = fmaxf(n0, __shfl_xor_sync(0xffffffffu, n0, 1)); n1 = fmaxf(n1, __shfl_xor_sync(0xffffffffu, n1, 1));
        n0 = fmaxf(n0, __shfl_xor_sync(0xffffffffu, n0, 2)); n1 = fmaxf(n1, __shfl_xor_sync(0xffffffffu, n1, 2));
        n0 = fmaxf(n0, m0); n1 = fmaxf(n1, m1);
        const float al0 = ex2(m0 - n0), al1 = ex2(m1 - n1);
        m0 = n0; m1 = n1;
        float e[8];
#pragma unroll
        for (int i = 0; i < 8; i++) e[i] = ex2(fmaf(sc[i], c, (i & 2) ? -n1 : -n0));
        l0 = l0 * al0 + (e[0] + e[1]) + (e[4] + e[5]);
        l1 = l1 * al1 + (e[2] + e[3]) + (e[6] + e[7]);
        const uint32_t p0 = pack_bf16(e[0], e[1]), p1 = pack_bf16(e[2], e[3]), p2 = pack_bf16(e[4], e[5]), p3 = pack_bf16(e[6], e[7]);
#pragma unroll
        for (int nb = 0; nb < 16; nb++) {
            const unsigned short* vp = (const unsigned short*)(vptr + (size_t)(k0 + (lane & 3) * 2) * 256) + nb * 8 + (lane >> 2);
            const uint32_t b0 = vp[0] | ((uint32_t)vp[128] << 16), b1 = vp[8 * 128] | ((uint32_t)vp[9 * 128] << 16);
            acc[4 * nb] *= al0; acc[4 * nb + 1] *= al0; acc[4 * nb + 2] *= al1; acc[4 * nb + 3] *= al1;
            mma_16816(acc + 4 * nb, p0, p1, p2, p3, b0, b1);
        }
    }
#pragma unroll
    for (int i = 0; i < 64; i++) o[i] = acc[i];
    ml[0] = m0; ml[1] = m1; ml[2] = l0; ml[3] = l1;
}

template <int S>
__device__ __forceinline__ void combine_and_store(float (&o)[64], float m0, float m1, float l0, float l1, uint32_t sb,
                                                  int wg, int warp, int lane, int tid, char* odst) {
    constexpr int KEEP = S * 32, SEND = 32 - KEEP;
    const uint32_t wbuf = sb + OFF_Q + wg * 16384 + warp * 4096;
    const uint32_t peer_buf = mapa(wbuf + lane * 16, S ^ 1);
    const uint32_t peer_ml = mapa(sb + OFF_ML + tid * 16, S ^ 1);
    const uint32_t peer_bar = mapa(sb + OFF_BAR + (BAR_XFULL + wg) * 8, S ^ 1);
    mbar_wait_cluster(sb + OFF_BAR + (BAR_XFREE + wg) * 8, 0);
    st_async_v4(peer_ml, m0, m1, l0, l1, peer_bar);
#pragma unroll
    for (int i = 0; i < 8; i++)
        st_async_v4(peer_buf + i * 512, o[SEND + 4 * i], o[SEND + 4 * i + 1], o[SEND + 4 * i + 2], o[SEND + 4 * i + 3], peer_bar);
    mbar_wait_cluster(sb + OFF_BAR + (BAR_XFULL + wg) * 8, 0);
    const float4 pml = lds_v4(sb + OFF_ML + tid * 16);
    const float mm0 = fmaxf(m0, pml.x), mm1 = fmaxf(m1, pml.y);
    float a0 = ex2(m0 - mm0), b0 = ex2(pml.x - mm0);
    float a1 = ex2(m1 - mm1), b1 = ex2(pml.y - mm1);
    const float inv0 = 1.0f / (a0 * l0 + b0 * pml.z), inv1 = 1.0f / (a1 * l1 + b1 * pml.w);
    a0 *= inv0; b0 *= inv0; a1 *= inv1; b1 *= inv1;
#pragma unroll
    for (int q = 0; q < 4; q++) {
        const float4 v = lds_v4(wbuf + lane * 16 + (2 * q) * 512), w = lds_v4(wbuf + lane * 16 + (2 * q + 1) * 512);
        const int i = KEEP + 8 * q;
        st_relaxed_v4(odst + q * 512, pack_nz(o[i] * a0 + v.x * b0, o[i + 1] * a0 + v.y * b0), pack_nz(o[i + 2] * a1 + v.z * b1, o[i + 3] * a1 + v.w * b1),
                      pack_nz(o[i + 4] * a0 + w.x * b0, o[i + 5] * a0 + w.y * b0), pack_nz(o[i + 6] * a1 + w.z * b1, o[i + 7] * a1 + w.w * b1));
    }
}

__device__ __forceinline__ int p3_kblock(int n) { return (n >> 2) * 2 + (n & 1) + ((n >> 1) & 1) * 8; }

__global__ void __cluster_dims__(2, 1, 1) __launch_bounds__(NTHREADS, 1)
gqa_fused_kernel(const __grid_constant__ CUtensorMap tm_x, const __grid_constant__ CUtensorMap tm_wq,
                 const __grid_constant__ CUtensorMap tm_k, const __grid_constant__ CUtensorMap tm_v,
                 const __grid_constant__ CUtensorMap tm_wo, const __grid_constant__ CUtensorMap tm_out,
                 __nv_bfloat16* __restrict__ out, const char* __restrict__ wq, const char* __restrict__ kc,
                 const char* __restrict__ vc, const char* __restrict__ wo) {
    extern __shared__ __align__(1024) unsigned char smem[];
    uint32_t sb = smem_u32(smem);
    asm volatile("mov.u32 %0, %0;" : "+r"(sb));
    const int tid = threadIdx.x, lane = tid & 31;
    const int wg = __shfl_sync(0xffffffffu, tid >> 7, 0), warp = __shfl_sync(0xffffffffu, (tid >> 5) & 3, 0);
    const int bid = blockIdx.x;
    const int mem = bid & 3, r = (bid >> 2) & 1, t = (bid >> 3) & 3, g = bid >> 5;
    const int s = mem & 1, b = 2 * t + (mem >> 1), col = bid & 7;
    const int head = g * 8 + r * 4 + mem;

    TL_INIT();
    if (wg == 3 && warp == 0) {
        if (elect_one()) {
            TL(0);
#pragma unroll
            for (int i = 0; i < NSLOT; i++) {
                mbar_init(sb + OFF_BAR + (BAR_FULL + i) * 8, 1);
                mbar_init(sb + OFF_BAR + (BAR_EMPTY + i) * 8, 12);
                mbar_init(sb + OFF_BAR + (BAR_OFULL + i) * 8, 4);
            }
#pragma unroll
            for (int i = 0; i < 3; i++) {
                mbar_init(sb + OFF_BAR + (BAR_XFREE + i) * 8, 4);
                mbar_init(sb + OFF_BAR + (BAR_XFULL + i) * 8, 1);
            }
            mbar_init(sb + OFF_BAR + BAR_GO2 * 8, 1);
            mbar_init(sb + OFF_BAR + (BAR_GO2 + 1) * 8, 1);
            mbar_init(sb + OFF_BAR + (BAR_GO2 + 2) * 8, 12);
            mbar_init(sb + OFF_BAR + (BAR_GO2 + 3) * 8, 1);
            asm volatile("fence.mbarrier_init.release.cluster;" ::: "memory");
            fence_async_smem();
#pragma unroll
            for (int f = 0; f < NSLOT; f++) {
                const uint32_t full = sb + OFF_BAR + (BAR_FULL + f) * 8, st = sb + OFF_RING + f * SLOT;
                mbar_expect_tx(full, 28672);
                tma_3d(st, &tm_wq, 0, f * 64, head * 2, full);
                tma_2d(st + 16384, &tm_x, f * 64, t * 96, full);
            }
#pragma unroll
            for (int f = NSLOT; f < NSLOT + PF_DIST; f++) l2_prefetch(wq + (size_t)f * 524288 + bid * 4096, 4096);
            TL(1);
        }
    } else if (wg == 3 && warp == 1) {
        if (elect_one()) { prefetch_tmap(&tm_k); prefetch_tmap(&tm_v); prefetch_tmap(&tm_wo); prefetch_tmap(&tm_out); }
    }
    __syncthreads();
    asm volatile("barrier.cluster.arrive.relaxed.aligned;" ::: "memory");

    if (wg == 3) {
        asm volatile("setmaxnreg.dec.sync.aligned.u32 32;");
        if (warp == 0) {
            if (elect_one()) {
                uint32_t bar = sb + OFF_BAR, st = sb + OFF_RING;
                uint32_t par = 0;
                auto advance = [&]() {
                    bar += 8; st += SLOT;
                    if (bar == sb + OFF_BAR + NSLOT * 8) { bar = sb + OFF_BAR; st = sb + OFF_RING; par ^= 1; }
                };
#pragma unroll 1
                for (int f = NSLOT; f < 16; f++) {
                    if (f == 15) {
                        mbar_wait(sb + OFF_BAR + (BAR_GO2 + 1) * 8, 0);
                        unsigned at;
                        asm volatile("ld.shared.u32 %0, [%1];" : "=r"(at) : "r"(sb + OFF_ZT) : "memory");
                        flag_wait(g_aflag + (bid >> 2) * 32, at);
                        mbar_arrive(sb + OFF_BAR + (BAR_GO2 + 3) * 8);
                    }
                    mbar_wait(bar + BAR_EMPTY * 8, par);
                    mbar_expect_tx(bar, 28672);
                    tma_3d(st, &tm_wq, 0, f * 64, head * 2, bar);
                    tma_2d(st + 16384, &tm_x, f * 64, t * 96, bar);
                    if (f + PF_DIST < 16) l2_prefetch(wq + (size_t)(f + PF_DIST) * 524288 + bid * 4096, 4096);
                    advance();
                }
                const int kvrow = (b * 4 + g) * 2048 + s * 1024;
                TL(2);
#pragma unroll 1
                for (int f = 0; f < 16; f++) {
                    if (f == KV_EARLY) { mbar_wait(sb + OFF_BAR + (BAR_GO2 + 2) * 8, 0); TL(3); }
                    if (f == 8) mbar_arrive(sb + OFF_BAR + BAR_GO2 * 8);
                    if (f == 15) {
                        mbar_wait(sb + OFF_BAR + (BAR_GO2 + 1) * 8, 1);
                        unsigned bt;
                        asm volatile("ld.shared.u32 %0, [%1];" : "=r"(bt) : "r"(sb + OFF_ZT + 4) : "memory");
                        flag_wait(g_bflag + t * 32, bt);
                        fence_async_all();
                    }
                    mbar_wait(bar + BAR_EMPTY * 8, par);
                    mbar_expect_tx(bar, 32768);
                    tma_3d(st, (f & 1) ? &tm_v : &tm_k, 0, kvrow + (f >> 1) * 128, 0, bar);
                    TL(16 + f);
                    if (f >= KV_EARLY && f < NSLOT) { const uint32_t t0 = clock32(); while ((int)(clock32() - t0) < KV_GAP) ; }
                    advance();
                }
#pragma unroll 1
                for (int f = 0; f < 16; f++) {
                    mbar_wait(bar + BAR_EMPTY * 8, par);
                    mbar_expect_tx(bar, 16384);
                    tma_3d(st, &tm_wo, 0, g * 1024 + p3_kblock(f) * 64, col * 2, bar);
                    advance();
                }
                TL(6);
            }
        } else if (warp == 1) {
            if (elect_one()) {
                uint32_t next = clock32() + PF_WO_START;
                mbar_wait(sb + OFF_BAR + (BAR_GO2 + 3) * 8, 0);
                {
                    uint32_t nx = clock32() + PF_KV_DELAY;
                    const size_t kvoff = ((size_t)((b * 4 + g) * 2048 + s * 1024 + r * 64)) * 256;
#pragma unroll 1
                    for (int c = KV_EARLY * (16384 / PF_CH); c < PF_KV_END * (16384 / PF_CH); c++) {
                        const int f = c / (16384 / PF_CH);
                        while ((int)(clock32() - nx) < 0) __nanosleep(40);
                        l2_prefetch(((f & 1) ? vc : kc) + kvoff + (size_t)(f >> 1) * 32768 + (c % (16384 / PF_CH)) * PF_CH, PF_CH);
                        nx += PF_KV_INT;
                    }
                }
#pragma unroll 1
                for (int i = 0; i < 16; i++) {
                    while ((int)(clock32() - next) < 0) __nanosleep(200);
                    l2_prefetch(wo + (size_t)g * 2097152 + (size_t)p3_kblock(i) * 131072 + (bid & 31) * 4096, 4096);
                    next += PF_WO_INTERVAL;
                }
                TL(7);
            }
        } else {
            const int i6 = tid & 63;
            unsigned* aflag = g_aflag + (bid >> 2) * 32;
            unsigned* bflag = g_bflag + t * 32;
            if (i6 == 0) {
                const unsigned av = ld_relaxed(aflag), bv = ld_relaxed(bflag);
                asm volatile("st.shared.v2.u32 [%0], {%1, %2};" ::"r"(sb + OFF_ZT), "r"((av / A_CNT + 1) * A_CNT), "r"((bv / B_CNT + 1) * B_CNT) : "memory");
            }
            uint4* qz = g_qbuf + (size_t)((b * 4 + g) * 2 + r) * 3072 + s * 1536 + i6;
#pragma unroll 1
            for (int k = 0; k < 24; k++) { qz[k * 64] = make_uint4(0, 0, 0, 0); if (CLR_SLEEP) __nanosleep(CLR_SLEEP); }
            bar_sync_n(4, 64);
            if (i6 == 0) { red_release(aflag, 1); mbar_arrive(sb + OFF_BAR + (BAR_GO2 + 1) * 8); }
            mbar_wait(sb + OFF_BAR + BAR_GO2 * 8, 0);
            uint4* oz = g_obuf + (size_t)(g * 4 + t) * 12288 + col * 1536 + i6;
#pragma unroll 1
            for (int k = 0; k < 24; k++) { oz[k * 64] = make_uint4(0, 0, 0, 0); __nanosleep(100); }
#pragma unroll
            for (int k = 0; k < 6; k++) {
                const int e = i6 + k * 64;
                *((uint4*)(out + (size_t)(t * 96 + g * 24 + (e >> 4)) * 1024 + col * 128) + (e & 15)) = make_uint4(0, 0, 0, 0);
            }
            bar_sync_n(4, 64);
            if (i6 == 0) { red_release(bflag, 1); mbar_arrive(sb + OFF_BAR + (BAR_GO2 + 1) * 8); }
        }
        __syncwarp();
        asm volatile("barrier.cluster.wait.aligned;" ::: "memory");
        TL_DUMP();
    } else {
        asm volatile("setmaxnreg.inc.sync.aligned.u32 160;");
        const uint32_t qpiece = sb + OFF_Q + wg * 16384;
        const int mi = lane >> 3;
        if (wg > 0) {
            float acc[48];
            proj_mainloop<false>(acc, sb, wg - 1, lane);
            if (tid == 128) TL(8);
#pragma unroll
            for (int bb = 0; bb < 2; bb++)
#pragma unroll
                for (int v = 0; v < 3; v++) {
                    const int j = 6 * bb + 2 * v;
                    char* dst = (char*)g_qbuf + (size_t)(((2 * t + bb) * 4 + g) * 2 + r) * 49152 + ((3 * mem + v) * 8 + (wg - 1) * 4 + warp) * 512 + lane * 16;
                    st_relaxed_v4(dst, pack_nz(acc[4 * j], acc[4 * j + 1]), pack_nz(acc[4 * j + 2], acc[4 * j + 3]),
                                  pack_nz(acc[4 * j + 4], acc[4 * j + 5]), pack_nz(acc[4 * j + 6], acc[4 * j + 7]));
                }
            if (tid == 128) TL(9);
        } else {
            mbar_wait(sb + OFF_BAR + (BAR_GO2 + 3) * 8, 0);
        }
        if ((tid & 127) == 0) mbar_expect_tx(sb + OFF_BAR + (BAR_XFULL + wg) * 8, 128 * 9 * 16);
        const char* qsrc = (const char*)g_qbuf + (size_t)((b * 4 + g) * 2 + r) * 49152 + (4 * wg + warp) * 4096 + lane * 16;
        {
            uint4 v[8];
            bool ok;
            do {
                probe_wait(qsrc - lane * 16 + (lane & 7) * 512);
                if (lane == 0 && warp == 0) TL(42 + wg);
                ok = true;
#pragma unroll
                for (int i = 0; i < 8; i++) v[i] = ld_relaxed_v4(qsrc + i * 512);
#pragma unroll
                for (int i = 0; i < 8; i++) ok = ok && valid4(v[i]);
            } while (!__all_sync(0xffffffffu, ok));
            const uint32_t a0 = qpiece + (16 * warp + (mi >> 1) * 8 + (lane & 7)) * 128;
#pragma unroll
            for (int i = 0; i < 8; i++)
                stsm_x4_t(a0 + (i >> 2) * 8192 + (((2 * (i & 3) + (mi & 1)) ^ (lane & 7)) << 4), v[i].x, v[i].y, v[i].z, v[i].w);
            fence_async_smem();
            if (lane == 0) mbar_arrive(sb + OFF_BAR + (BAR_GO2 + 2) * 8);
            named_sync(1 + wg);
        }
        asm volatile("barrier.cluster.wait.aligned;" ::: "memory");

        {
            const float c = 0.08838834764831845f * 1.4426950408889634f;
            float o[64];
            float m0 = 0.f, m1 = 0.f, l0 = 0.f, l1 = 0.f;
            if (lane == 0 && warp == 0) TL(10 + wg);
            const uint64_t dq = mkdesc(qpiece, 0, 1024);
#pragma unroll 1
            for (int j = 0; j < 8; j++) {
                float sc[64];
                const uint32_t kslot = (0x03142031u >> (4 * j)) & 7, vslot = (0x14203142u >> (4 * j)) & 7;
                TLC(j * 6 + 0);
                mbar_wait(sb + OFF_BAR + (BAR_FULL + kslot) * 8, (0x63u >> j) & 1);
                TLC(j * 6 + 1);
                {
                    const uint64_t dk = mkdesc(sb + OFF_RING + kslot * SLOT, 0, 1024);
                    wg_fence();
#pragma unroll
                    for (int kk = 0; kk < 8; kk++)
                        wgmma_n128_ss<0, 0>(sc, dq + (kk >> 2) * (8192 >> 4) + (kk & 3) * 2, dk + (kk >> 2) * (16384 >> 4) + (kk & 3) * 2, kk != 0);
                    wg_commit();
                    wg_wait<0>();
                    reg_fence(sc);
                }
                TLC(j * 6 + 2);
                if (lane == 0) mbar_arrive(sb + OFF_BAR + (BAR_EMPTY + kslot) * 8);
                if (j == 0) {
                    float x0 = fmaxf(sc[0], sc[1]), x1 = fmaxf(sc[2], sc[3]), y0 = fmaxf(sc[4], sc[5]), y1 = fmaxf(sc[6], sc[7]);
#pragma unroll
                    for (int i = 8; i < 64; i += 8) {
                        x0 = fmaxf(x0, fmaxf(sc[i], sc[i + 1])); x1 = fmaxf(x1, fmaxf(sc[i + 2], sc[i + 3]));
                        y0 = fmaxf(y0, fmaxf(sc[i + 4], sc[i + 5])); y1 = fmaxf(y1, fmaxf(sc[i + 6], sc[i + 7]));
                    }
                    x0 = fmaxf(x0, y0); x1 = fmaxf(x1, y1);
                    x0 = fmaxf(x0, __shfl_xor_sync(0xffffffffu, x0, 1)); x1 = fmaxf(x1, __shfl_xor_sync(0xffffffffu, x1, 1));
                    x0 = fmaxf(x0, __shfl_xor_sync(0xffffffffu, x0, 2)); x1 = fmaxf(x1, __shfl_xor_sync(0xffffffffu, x1, 2));
                    m0 = x0 * c; m1 = x1 * c;
                }
                if (j == 7 && lane == 0) mbar_arrive_remote(mapa(sb + OFF_BAR + (BAR_XFREE + wg) * 8, s ^ 1));
                uint32_t p[32];
                TLC(j * 6 + 3);
                mbar_wait(sb + OFF_BAR + (BAR_FULL + vslot) * 8, (0x73u >> j) & 1);
                TLC(j * 6 + 4);
                const uint64_t dv = mkdesc(sb + OFF_RING + vslot * SLOT, 16384, 1024);
#pragma unroll
                for (int ch = 0; ch < 2; ch++) {
#pragma unroll
                    for (int i = ch * 8; i < ch * 8 + 8; i++) {
                        const float e0 = ex2(fmaf(sc[4 * i], c, -m0)), e1 = ex2(fmaf(sc[4 * i + 1], c, -m0));
                        const float e2 = ex2(fmaf(sc[4 * i + 2], c, -m1)), e3 = ex2(fmaf(sc[4 * i + 3], c, -m1));
                        p[2 * i] = pack_bf16(e0, e1);
                        p[2 * i + 1] = pack_bf16(e2, e3);
                    }
                    wg_fence();
#pragma unroll
                    for (int kk = ch * 4; kk < ch * 4 + 4; kk++)
                        wgmma_n128_rs<1>(o, p[4 * kk], p[4 * kk + 1], p[4 * kk + 2], p[4 * kk + 3], dv + kk * (2048 >> 4), (j | kk) != 0);
                    wg_commit();
                    const uint32_t* q = p + ch * 16;
                    const uint32_t a = hadd2(hadd2(hadd2(q[0], q[2]), hadd2(q[4], q[6])), hadd2(hadd2(q[8], q[10]), hadd2(q[12], q[14])));
                    const uint32_t d = hadd2(hadd2(hadd2(q[1], q[3]), hadd2(q[5], q[7])), hadd2(hadd2(q[9], q[11]), hadd2(q[13], q[15])));
                    l0 += __uint_as_float(a << 16) + __uint_as_float(a & 0xffff0000u);
                    l1 += __uint_as_float(d << 16) + __uint_as_float(d & 0xffff0000u);
                }
                wg_wait<0>();
                reg_fence(o);
                if (lane == 0) mbar_arrive(sb + OFF_BAR + (BAR_EMPTY + vslot) * 8);
                TLC(j * 6 + 5);
            }

            if (__any_sync(0xffffffffu, !(l0 <= L_SAFE && l1 <= L_SAFE))) {
                float fo[64], fml[4];
                const size_t kvoff = (size_t)((b * 4 + g) * 2048 + s * 1024) * 256;
                const char* qs = (const char*)g_qbuf + (size_t)((b * 4 + g) * 2 + r) * 49152 + (4 * wg + warp) * 4096 + (threadIdx.x & 31) * 16;
                attention_fallback(fo, fml, qs, kc + kvoff, vc + kvoff, c);
#pragma unroll
                for (int i = 0; i < 64; i++) o[i] = fo[i];
                m0 = fml[0]; m1 = fml[1]; l0 = fml[2]; l1 = fml[3];
            }
            l0 += __shfl_xor_sync(0xffffffffu, l0, 1); l1 += __shfl_xor_sync(0xffffffffu, l1, 1);
            l0 += __shfl_xor_sync(0xffffffffu, l0, 2); l1 += __shfl_xor_sync(0xffffffffu, l1, 2);
            const int u = 4 * wg + warp;
            char* odst = (char*)g_obuf + (size_t)((g * 4 + t) * 16 + (4 * r + u / 3) * 2 + s) * 12288 + ((b & 1) * 3 + u % 3) * 2048 + lane * 16;
            if (s == 0) combine_and_store<0>(o, m0, m1, l0, l1, sb, wg, warp, lane, tid, odst);
            else combine_and_store<1>(o, m0, m1, l0, l1, sb, wg, warp, lane, tid, odst);
            if (lane == 0 && warp == 0) TL(13 + wg);
        }

        if (wg == 0) {
            const char* osrc = (const char*)g_obuf + (size_t)(g * 4 + t) * 196608 + warp * 3072 + lane * 16;
            uint4 va[12], vb[12];
            auto load = [&](uint4 (&v)[12], int n) {
#pragma unroll
                for (int y = 0; y < 12; y++) v[y] = ld_relaxed_v4(osrc + p3_kblock(2 * n + y / 6) * 12288 + (y % 6) * 512);
            };
            auto finish = [&](uint4 (&v)[12], int n) {
                while (true) {
                    bool ok = true;
#pragma unroll
                    for (int y = 0; y < 12; y++) ok = ok && valid4(v[y]);
                    if (__all_sync(0xffffffffu, ok)) break;
                    probe_wait(osrc - lane * 16 + p3_kblock(2 * n + ((lane >> 1) & 1)) * 12288 + (lane & 1) * 5 * 512);
                    load(v, n);
                }
#pragma unroll
                for (int h = 0; h < 2; h++) {
                    const int f = 32 + 2 * n + h, slot = f % NSLOT;
                    mbar_wait(sb + OFF_BAR + (BAR_EMPTY + slot) * 8, ((f / NSLOT) & 1) ^ 1);
#pragma unroll
                    for (int y = 0; y < 6; y++) {
                        const int z = warp * 6 + y;
                        const uint32_t a = sb + OFF_RING + slot * SLOT + 16384 + ((z >> 2) * 16 + (mi & 1) * 8 + (lane & 7)) * 128 +
                                           (((2 * (z & 3) + (mi >> 1)) ^ (lane & 7)) << 4);
                        stsm_x4(a, v[6 * h + y].x, v[6 * h + y].y, v[6 * h + y].z, v[6 * h + y].w);
                    }
                    fence_async_smem();
                    __syncwarp();
                    if (lane == 0) mbar_arrive(sb + OFF_BAR + (BAR_OFULL + slot) * 8);
                }
                if (n == 0 && tid == 0) TL(4);
                if (n == 7 && tid == 0) TL(5);
            };
            probe_wait(osrc - lane * 16 + p3_kblock((lane >> 1) & 1) * 12288 + (lane & 1) * 5 * 512);
            load(va, 0);
#pragma unroll
            for (int n = 0; n < 8; n += 2) {
                load(vb, n + 1);
                finish(va, n);
                if (n + 2 < 8) load(va, n + 2);
                finish(vb, n + 1);
            }
        } else {
            float acc[48];
            proj_mainloop<true>(acc, sb, wg - 1, lane);
            if (tid == 128) TL(40);
            named_sync(1 + wg);
            const uint32_t a0 = qpiece + ((mi >> 1) * 8 + (lane & 7)) * 128 + (((2 * warp + (mi & 1)) ^ (lane & 7)) << 4);
#pragma unroll
            for (int j = 0; j < 12; j += 2)
                stsm_x4_t(a0 + j * 1024, pack_bf16(acc[4 * j], acc[4 * j + 1]), pack_bf16(acc[4 * j + 2], acc[4 * j + 3]),
                          pack_bf16(acc[4 * j + 4], acc[4 * j + 5]), pack_bf16(acc[4 * j + 6], acc[4 * j + 7]));
            fence_async_smem();
            named_sync(1 + wg);
            if (warp == 0 && elect_one()) {
                tma_reduce_add_2d(&tm_out, col * 128 + (wg - 1) * 64, t * 96, qpiece);
                bulk_commit();
                bulk_wait0_read();
                if (wg == 1) TL(41);
            }
            __syncwarp();
        }
        TL_DUMP();
    }
}

typedef CUresult (*EncodeFn)(CUtensorMap*, CUtensorMapDataType, cuuint32_t, void*, const cuuint64_t*, const cuuint64_t*,
                             const cuuint32_t*, const cuuint32_t*, CUtensorMapInterleave, CUtensorMapSwizzle,
                             CUtensorMapL2promotion, CUtensorMapFloatOOBfill);

void make_map(EncodeFn enc, CUtensorMap* m, const void* ptr, int rank, uint64_t rows, uint64_t cols, uint32_t box_rows) {
    cuuint64_t dims[3] = {rank == 2 ? cols : 64, rows, cols / 64};
    cuuint64_t strides[2] = {cols * 2, 128};
    cuuint32_t box[3] = {64, box_rows, 2};
    cuuint32_t es[3] = {1, 1, 1};
    enc(m, CU_TENSOR_MAP_DATA_TYPE_BFLOAT16, rank, const_cast<void*>(ptr), dims, strides, box, es, CU_TENSOR_MAP_INTERLEAVE_NONE,
        CU_TENSOR_MAP_SWIZZLE_128B, CU_TENSOR_MAP_L2_PROMOTION_L2_256B, CU_TENSOR_MAP_FLOAT_OOB_FILL_NONE);
}

}

extern "C" void kernel_launch(void* const* d_in, const int* in_sizes, int n_in, void* d_out, int out_size) {
    (void)in_sizes; (void)n_in; (void)out_size;
    static EncodeFn enc = nullptr;
    static int grid = NCTA;
    if (!enc) {
        void* fn = nullptr;
        cudaDriverEntryPointQueryResult qr;
        cudaGetDriverEntryPoint("cuTensorMapEncodeTiled", &fn, cudaEnableDefault, &qr);
        enc = (EncodeFn)fn;
        cudaFuncSetAttribute(gqa_fused_kernel, cudaFuncAttributeMaxDynamicSharedMemorySize, SMEM_TOTAL);
        cudaLaunchConfig_t cfg = {};
        cfg.gridDim = dim3(NCTA + 4);
        cfg.blockDim = dim3(NTHREADS);
        cfg.dynamicSmemBytes = SMEM_TOTAL;
        cudaLaunchAttribute at;
        at.id = cudaLaunchAttributeClusterDimension;
        at.val.clusterDim.x = 2; at.val.clusterDim.y = 1; at.val.clusterDim.z = 1;
        cfg.attrs = &at;
        cfg.numAttrs = 1;
        int ncl = 0;
        if (cudaOccupancyMaxActiveClusters(&ncl, gqa_fused_kernel, &cfg) == cudaSuccess && ncl >= NCTA / 2 + 2) grid = NCTA + 4;
        (void)cudaGetLastError();
    }
    CUtensorMap tx, twq, tk, tv, two, tout;
    make_map(enc, &tx, d_in[0], 2, 384, 1024, 48);
    make_map(enc, &tk, d_in[1], 3, 65536, 128, 128);
    make_map(enc, &tv, d_in[2], 2, 65536, 128, 128);
    {
        cuuint64_t dims[4] = {64, 1024, 2, 32};
        cuuint64_t strides[3] = {8192, 128, 256};
        cuuint32_t box[4] = {64, 64, 1, 4};
        cuuint32_t es[4] = {1, 1, 1, 1};
        enc(&twq, CU_TENSOR_MAP_DATA_TYPE_BFLOAT16, 4, d_in[3], dims, strides, box, es, CU_TENSOR_MAP_INTERLEAVE_NONE,
            CU_TENSOR_MAP_SWIZZLE_128B, CU_TENSOR_MAP_L2_PROMOTION_L2_256B, CU_TENSOR_MAP_FLOAT_OOB_FILL_NONE);
    }
    make_map(enc, &two, d_in[4], 3, 4096, 1024, 64);
    make_map(enc, &tout, d_out, 2, 384, 1024, 48);
    gqa_fused_kernel<<<grid, NTHREADS, SMEM_TOTAL, cudaStreamPerThread>>>(tx, twq, tk, tv, two, tout, (__nv_bfloat16*)d_out,
        (const char*)d_in[0], (const char*)d_in[3], (const char*)d_in[1], (const char*)d_in[2], (const char*)d_in[4]);
}
```

```cpp
#include <cuda_runtime.h>
#include <cuda_bf16.h>
#include <cuda.h>
#include <stdint.h>

namespace {

constexpr int NCTA = 128;
constexpr int NTHREADS = 512;
constexpr int SLOT = 32768;
constexpr int NSLOT = 5;
constexpr int OFF_ZERO = 0;
constexpr int OFF_Q = 8192;
constexpr int OFF_ML = OFF_Q + 49152;
constexpr int OFF_RING = OFF_ML + 6144;
constexpr int OFF_BAR = OFF_RING + NSLOT * SLOT;
constexpr int SMEM_BYTES = OFF_BAR + 576;
constexpr int NS1 = 6, OFF_X1 = 38912;
constexpr int NW3 = 9, NO3 = 6;
constexpr int BAR_FULL = 0, BAR_EMPTY = 5,
              BAR_FULL1 = 10, BAR_EMPTY1 = 16, BAR_EMPTY3 = 22,
              BAR_XFREE = 28, BAR_CDONE = 31,
              BAR_GO2 = 34,
              BAR_ONES = 35, BAR_XFULL = 35, BAR_XML = 38, BAR_QFULL = 41, BAR_QFREE = 44, BAR_BOK = 46, BAR_GRP = 47,
              BAR_FULL3 = 49, BAR_OFULL = 55, BAR_WFULL = 61, BAR_END = 70;

constexpr unsigned B_CNT = NCTA;
#define PLACE 1
#define SCHED 3
#define ARR_CH 0
#define ARR_L 1
#define NCHK 2
#define CHB 0x850
#define WSTEP 2
#define GO2_AT 9
#define CLR_GAP 500
#define H_SEQ 0x10
#define H_KV_N 2
#define H_START 2000
#define H_KV_INT 500
#define H_WO_START 24000
#define H_WO_INT 500
#define RMAP 0
#define PROMO_KV 2
#define PROMO_W 3
#define MAXN 32
#define KV_GAP 600
constexpr int SPIN_LIMIT = 1 << 22;
constexpr float SCALE_LOG2E = 0.08838834764831845f * 1.4426950408889634f;
constexpr float L_SAFE = 1.1258999e15f;

__device__ uint4 g_oimg[16 * 16 * 12288 / 16];
__device__ unsigned g_bflag[32];

__device__ __forceinline__ void TL(int) {}
__device__ __forceinline__ void TLP(int, uint32_t, int) {}
#define TLC(idx)
#define TLF(idx)
#define TLPF(c, sb, idx)
#define STALL_BEGIN()
#define STALL_END(idx)
#define TL_INIT()
#define TL_DUMP()
#define TL_DONE()
constexpr int SMEM_TOTAL = SMEM_BYTES;

__device__ __forceinline__ uint32_t smem_u32(const void* p) { return (uint32_t)__cvta_generic_to_shared(p); }
__device__ __forceinline__ void mbar_init(uint32_t bar, uint32_t cnt) {
    asm volatile("mbarrier.init.shared::cta.b64 [%0], %1;" ::"r"(bar), "r"(cnt) : "memory");
}
__device__ __forceinline__ void mbar_expect_tx(uint32_t bar, uint32_t bytes) {
    asm volatile("mbarrier.arrive.expect_tx.shared::cta.b64 _, [%0], %1;" ::"r"(bar), "r"(bytes) : "memory");
}
__device__ __forceinline__ void mbar_arrive(uint32_t bar) {
    asm volatile("mbarrier.arrive.shared::cta.b64 _, [%0];" ::"r"(bar) : "memory");
}
__device__ __forceinline__ void mbar_arrive_cnt(uint32_t bar, uint32_t cnt) {
    asm volatile("mbarrier.arrive.shared::cta.b64 _, [%0], %1;" ::"r"(bar), "r"(cnt) : "memory");
}
__device__ __forceinline__ void mbar_arrive_remote(uint32_t cluster_addr) {
    asm volatile("fence.release.sync_restrict::shared::cta.cluster;\n"
                 "mbarrier.arrive.relaxed.cluster.shared::cluster.b64 _, [%0];" ::"r"(cluster_addr) : "memory");
}
#define SPIN_GUARD(it) asm volatile("{\n.reg .pred q;\nsetp.gt.s32 q, %0, %1;\n@q trap;\n}" ::"r"(it), "n"(SPIN_LIMIT));
__device__ __forceinline__ void (mbar_wait)(uint32_t bar, uint32_t parity) {
    asm volatile(
        "{\n.reg .pred p, q;\n.reg .u32 c;\nmov.u32 c, 0;\n"
        "WAIT_LOOP:\n"
        "mbarrier.try_wait.parity.shared::cta.b64 p, [%0], %1;\n"
        "@p bra WAIT_DONE;\n"
        "add.u32 c, c, 1;\nsetp.gt.u32 q, c, %2;\n@q trap;\n"
        "bra WAIT_LOOP;\n"
        "WAIT_DONE:\n}\n" ::"r"(bar), "r"(parity), "n"(SPIN_LIMIT) : "memory");
}
__device__ __forceinline__ void (mbar_wait_cluster)(uint32_t bar, uint32_t parity) {
    asm volatile(
        "{\n.reg .pred p, q;\n.reg .u32 c;\nmov.u32 c, 0;\n"
        "WAIT_LOOP:\n"
        "mbarrier.try_wait.parity.acquire.cluster.shared::cta.b64 p, [%0], %1;\n"
        "@p bra WAIT_DONE;\n"
        "add.u32 c, c, 1;\nsetp.gt.u32 q, c, %2;\n@q trap;\n"
        "bra WAIT_LOOP;\n"
        "WAIT_DONE:\n}\n" ::"r"(bar), "r"(parity), "n"(SPIN_LIMIT) : "memory");
}
__device__ __forceinline__ bool elect_one() {
    uint32_t el;
    asm volatile("{\n.reg .pred p;\nelect.sync _|p, 0xffffffff;\nselp.u32 %0, 1, 0, p;\n}" : "=r"(el));
    return el != 0;
}
__device__ __forceinline__ void prefetch_tmap(const CUtensorMap* tm) { asm volatile("prefetch.tensormap [%0];" ::"l"(tm) : "memory"); }
__device__ __forceinline__ uint32_t mapa(uint32_t addr, uint32_t rank) {
    uint32_t r;
    asm("mapa.shared::cluster.u32 %0, %1, %2;" : "=r"(r) : "r"(addr), "r"(rank));
    return r;
}
__device__ __forceinline__ void tma_2d(uint32_t dst, const CUtensorMap* tm, int c0, int c1, uint32_t bar) {
    asm volatile("cp.async.bulk.tensor.2d.shared::cluster.global.mbarrier::complete_tx::bytes [%0], [%1, {%3, %4}], [%2];"
                 ::"r"(dst), "l"(tm), "r"(bar), "r"(c0), "r"(c1) : "memory");
}
__device__ __forceinline__ void tma_3d(uint32_t dst, const CUtensorMap* tm, int c0, int c1, int c2, uint32_t bar) {
    asm volatile("cp.async.bulk.tensor.3d.shared::cluster.global.mbarrier::complete_tx::bytes [%0], [%1, {%3, %4, %5}], [%2];"
                 ::"r"(dst), "l"(tm), "r"(bar), "r"(c0), "r"(c1), "r"(c2) : "memory");
}
__device__ __forceinline__ void tma_4d(uint32_t dst, const CUtensorMap* tm, int c0, int c1, int c2, int c3, uint32_t bar) {
    asm volatile("cp.async.bulk.tensor.4d.shared::cluster.global.mbarrier::complete_tx::bytes [%0], [%1, {%3, %4, %5, %6}], [%2];"
                 ::"r"(dst), "l"(tm), "r"(bar), "r"(c0), "r"(c1), "r"(c2), "r"(c3) : "memory");
}
__device__ __forceinline__ void bulk_s2peer(uint32_t dst_cluster, uint32_t src, uint32_t bytes, uint32_t bar_cluster) {
    asm volatile("cp.async.bulk.shared::cluster.shared::cta.mbarrier::complete_tx::bytes [%0], [%1], %2, [%3];"
                 ::"r"(dst_cluster), "r"(src), "r"(bytes), "r"(bar_cluster) : "memory");
}
__device__ __forceinline__ void bulk_g2s(uint32_t dst, const void* src, uint32_t bytes, uint32_t bar) {
    asm volatile("cp.async.bulk.shared::cluster.global.mbarrier::complete_tx::bytes [%0], [%1], %2, [%3];"
                 ::"r"(dst), "l"(src), "r"(bytes), "r"(bar) : "memory");
}
__device__ __forceinline__ void bulk_s2g(void* dst, uint32_t src, uint32_t bytes) {
    asm volatile("cp.async.bulk.global.shared::cta.bulk_group [%0], [%1], %2;" ::"l"(dst), "r"(src), "r"(bytes) : "memory");
}
__device__ __forceinline__ void tma_reduce_add_2d(const CUtensorMap* tm, int c0, int c1, uint32_t src) {
    asm volatile("cp.reduce.async.bulk.tensor.2d.global.shared::cta.add.tile.bulk_group [%0, {%2, %3}], [%1];"
                 ::"l"(tm), "r"(src), "r"(c0), "r"(c1) : "memory");
}
__device__ __forceinline__ void l2_prefetch(const void* src, uint32_t bytes) {
    asm volatile("cp.async.bulk.prefetch.L2.global [%0], %1;" ::"l"(src), "r"(bytes) : "memory");
}
__device__ __forceinline__ uint32_t clock32() {
    uint32_t c;
    asm volatile("mov.u32 %0, %%clock;" : "=r"(c)::"memory");
    return c;
}
__device__ __forceinline__ void bulk_commit() { asm volatile("cp.async.bulk.commit_group;" ::: "memory"); }
__device__ __forceinline__ void bulk_wait0() { asm volatile("cp.async.bulk.wait_group 0;" ::: "memory"); }
__device__ __forceinline__ void bulk_wait0_read() { asm volatile("cp.async.bulk.wait_group.read 0;" ::: "memory"); }
__device__ __forceinline__ void fence_async_smem() { asm volatile("fence.proxy.async.shared::cta;" ::: "memory"); }
__device__ __forceinline__ void fence_async_all() { asm volatile("fence.proxy.async;" ::: "memory"); }
__device__ __forceinline__ void red_release(unsigned* p, unsigned v) {
    asm volatile("red.release.gpu.global.add.u32 [%0], %1;" ::"l"(p), "r"(v) : "memory");
}
__device__ __forceinline__ unsigned ld_acquire(const unsigned* p) {
    unsigned v;
    asm volatile("ld.acquire.gpu.global.u32 %0, [%1];" : "=r"(v) : "l"(p) : "memory");
    return v;
}
__device__ __forceinline__ unsigned ld_relaxed(const unsigned* p) {
    unsigned v;
    asm volatile("ld.relaxed.gpu.global.u32 %0, [%1];" : "=r"(v) : "l"(p) : "memory");
    return v;
}
__device__ __forceinline__ void (flag_wait)(const unsigned* p, unsigned target) {
    asm volatile(
        "{\n.reg .pred p, q;\n.reg .u32 c, v;\nmov.u32 c, 0;\n"
        "FLAG_LOOP:\n"
        "ld.acquire.gpu.global.u32 v, [%0];\n"
        "sub.u32 v, v, %1;\nsetp.ge.s32 p, v, 0;\n"
        "@p bra FLAG_DONE;\n"
        "add.u32 c, c, 1;\nsetp.gt.u32 q, c, %2;\n@q trap;\n"
        "bra FLAG_LOOP;\n"
        "FLAG_DONE:\n}\n" ::"l"(p), "r"(target), "n"(SPIN_LIMIT) : "memory");
}
__device__ __forceinline__ void named_sync(int id) { asm volatile("bar.sync %0, 128;" ::"r"(id) : "memory"); }
__device__ __forceinline__ void wg_fence() { asm volatile("wgmma.fence.sync.aligned;" ::: "memory"); }
__device__ __forceinline__ void wg_commit() { asm volatile("wgmma.commit_group.sync.aligned;" ::: "memory"); }
template <int N> __device__ __forceinline__ void wg_wait() { asm volatile("wgmma.wait_group.sync.aligned %0;" ::"n"(N) : "memory"); }
template <int N> __device__ __forceinline__ void reg_fence(float (&d)[N]) {
#pragma unroll
    for (int i = 0; i < N; i++) asm volatile("" : "+f"(d[i])::"memory");
}
__device__ __forceinline__ uint64_t mkdesc(uint32_t addr, uint32_t lbo, uint32_t sbo) {
    return (uint64_t)((addr & 0x3FFFF) >> 4) | ((uint64_t)(lbo >> 4) << 16) | ((uint64_t)(sbo >> 4) << 32) | (1ull << 62);
}
__device__ __forceinline__ uint32_t pack_bf16(float lo, float hi) {
    uint32_t r;
    asm("cvt.rn.bf16x2.f32 %0, %1, %2;" : "=r"(r) : "f"(hi), "f"(lo));
    return r;
}
__device__ __forceinline__ uint32_t hadd2(uint32_t a, uint32_t b) {
    uint32_t r;
    asm("add.rn.bf16x2 %0, %1, %2;" : "=r"(r) : "r"(a), "r"(b));
    return r;
}
__device__ __forceinline__ float ex2(float x) {
    float y;
    asm("ex2.approx.ftz.f32 %0, %1;" : "=f"(y) : "f"(x));
    return y;
}
__device__ __forceinline__ void stsm_x4(uint32_t addr, uint32_t r0, uint32_t r1, uint32_t r2, uint32_t r3) {
    asm volatile("stmatrix.sync.aligned.m8n8.x4.shared.b16 [%0], {%1, %2, %3, %4};" ::"r"(addr), "r"(r0), "r"(r1), "r"(r2), "r"(r3) : "memory");
}
__device__ __forceinline__ void stsm_x4_t(uint32_t addr, uint32_t r0, uint32_t r1, uint32_t r2, uint32_t r3) {
    asm volatile("stmatrix.sync.aligned.m8n8.x4.trans.shared.b16 [%0], {%1, %2, %3, %4};" ::"r"(addr), "r"(r0), "r"(r1), "r"(r2), "r"(r3) : "memory");
}
__device__ __forceinline__ void st_async_v4(uint32_t addr, float a, float b, float c, float d, uint32_t bar) {
    asm volatile("st.async.weak.shared::cluster.mbarrier::complete_tx::bytes.v4.f32 [%0], {%1, %2, %3, %4}, [%5];"
                 ::"r"(addr), "f"(a), "f"(b), "f"(c), "f"(d), "r"(bar) : "memory");
}
__device__ __forceinline__ void st_async_v4u(uint32_t addr, uint32_t a, uint32_t b, uint32_t c, uint32_t d, uint32_t bar) {
    asm volatile("st.async.weak.shared::cluster.mbarrier::complete_tx::bytes.v4.b32 [%0], {%1, %2, %3, %4}, [%5];"
                 ::"r"(addr), "r"(a), "r"(b), "r"(c), "r"(d), "r"(bar) : "memory");
}
__device__ __forceinline__ uint32_t lds_u32(uint32_t addr) {
    uint32_t v;
    asm volatile("ld.shared.u32 %0, [%1];" : "=r"(v) : "r"(addr) : "memory");
    return v;
}
__device__ __forceinline__ float rcp_fast(float x) {
    float y;
    asm("rcp.approx.ftz.f32 %0, %1;" : "=f"(y) : "f"(x));
    return y;
}
__device__ __forceinline__ float bf_lo(uint32_t w) { return __uint_as_float(w << 16); }
__device__ __forceinline__ float bf_hi(uint32_t w) { return __uint_as_float(w & 0xffff0000u); }
__device__ __forceinline__ float4 lds_v4(uint32_t addr) {
    float4 v;
    asm volatile("ld.shared.v4.f32 {%0, %1, %2, %3}, [%4];" : "=f"(v.x), "=f"(v.y), "=f"(v.z), "=f"(v.w) : "r"(addr) : "memory");
    return v;
}

__device__ __forceinline__ uint4 ld_relaxed_v4(const void* p) {
    uint4 v;
    asm volatile("ld.relaxed.gpu.global.v4.u32 {%0, %1, %2, %3}, [%4];" : "=r"(v.x), "=r"(v.y), "=r"(v.z), "=r"(v.w) : "l"(p) : "memory");
    return v;
}
__device__ __forceinline__ void st_relaxed_v4(void* p, uint32_t a, uint32_t b, uint32_t c, uint32_t d) {
    asm volatile("st.relaxed.gpu.global.v4.u32 [%0], {%1, %2, %3, %4};" ::"l"(p), "r"(a), "r"(b), "r"(c), "r"(d) : "memory");
}
__device__ __forceinline__ uint32_t pack_nz(float lo, float hi) {
    const uint32_t w = pack_bf16(lo, hi);
    return w == 0u ? 0x80008000u : w;
}
__device__ __forceinline__ bool valid4(const uint4& v) { return min(min(v.x, v.y), min(v.z, v.w)) != 0u; }
__device__ __forceinline__ void (probe_wait)(const void* p) {
    asm volatile(
        "{\n.reg .pred p, q;\n.reg .u32 c, v;\nmov.u32 c, 0;\n"
        "PROBE_LOOP:\n"
        "ld.relaxed.gpu.global.u32 v, [%0];\n"
        "setp.ne.u32 p, v, 0;\n"
        "vote.sync.all.pred p, p, 0xffffffff;\n"
        "@p bra PROBE_DONE;\n"
        "add.u32 c, c, 1;\nsetp.gt.u32 q, c, %1;\n@q trap;\n"
        "bra PROBE_LOOP;\n"
        "PROBE_DONE:\n}\n" ::"l"(p), "n"(SPIN_LIMIT) : "memory");
}
__device__ __forceinline__ void bar_sync_n(int id, int n) { asm volatile("bar.sync %0, %1;" ::"r"(id), "r"(n) : "memory"); }
__device__ __forceinline__ void bar_arrive_n(int id, int n) { asm volatile("bar.arrive %0, %1;" ::"r"(id), "r"(n) : "memory"); }
__device__ __forceinline__ uint32_t movm_t(uint32_t a) {
    uint32_t d;
    asm volatile("movmatrix.sync.aligned.m8n8.trans.b16 %0, %1;" : "=r"(d) : "r"(a));
    return d;
}
__device__ __forceinline__ void mma_16816(float* d, uint32_t a0, uint32_t a1, uint32_t a2, uint32_t a3, uint32_t b0, uint32_t b1) {
    asm volatile("mma.sync.aligned.m16n8k16.row.col.f32.bf16.bf16.f32 {%0, %1, %2, %3}, {%4, %5, %6, %7}, {%8, %9}, {%0, %1, %2, %3};"
                 : "+f"(d[0]), "+f"(d[1]), "+f"(d[2]), "+f"(d[3]) : "r"(a0), "r"(a1), "r"(a2), "r"(a3), "r"(b0), "r"(b1));
}

template <int V> struct Int { static constexpr int value = V; };

template <int TA, int TB>
__device__ __forceinline__ void wgmma_n48_ss(float (&d)[24], uint64_t da, uint64_t db, int scale_d) {
    asm volatile("{\n.reg .pred p;\nsetp.ne.b32 p, %26, 0;\n"
        "wgmma.mma_async.sync.aligned.m64n48k16.f32.bf16.bf16 {"
        "%0, %1, %2, %3, %4, %5, %6, %7, %8, %9, %10, %11, %12, %13, %14, %15, "
        "%16, %17, %18, %19, %20, %21, %22, %23}, "
        "%24, %25, p, 1, 1, %27, %28;\n}\n"
        : "+f"(d[0]), "+f"(d[1]), "+f"(d[2]), "+f"(d[3]), "+f"(d[4]), "+f"(d[5]), "+f"(d[6]), "+f"(d[7]),
          "+f"(d[8]), "+f"(d[9]), "+f"(d[10]), "+f"(d[11]), "+f"(d[12]), "+f"(d[13]), "+f"(d[14]), "+f"(d[15]),
          "+f"(d[16]), "+f"(d[17]), "+f"(d[18]), "+f"(d[19]), "+f"(d[20]), "+f"(d[21]), "+f"(d[22]), "+f"(d[23])
        : "l"(da), "l"(db), "r"(scale_d), "n"(TA), "n"(TB));
}
template <int TA, int TB>
__device__ __forceinline__ void wgmma_n96_ss(float (&d)[48], uint64_t da, uint64_t db, int scale_d) {
    asm volatile("{\n.reg .pred p;\nsetp.ne.b32 p, %50, 0;\n"
        "wgmma.mma_async.sync.aligned.m64n96k16.f32.bf16.bf16 {"
        "%0, %1, %2, %3, %4, %5, %6, %7, %8, %9, %10, %11, %12, %13, %14, %15, "
        "%16, %17, %18, %19, %20, %21, %22, %23, %24, %25, %26, %27, %28, %29, %30, %31, "
        "%32, %33, %34, %35, %36, %37, %38, %39, %40, %41, %42, %43, %44, %45, %46, %47}, "
        "%48, %49, p, 1, 1, %51, %52;\n}\n"
        : "+f"(d[0]), "+f"(d[1]), "+f"(d[2]), "+f"(d[3]), "+f"(d[4]), "+f"(d[5]), "+f"(d[6]), "+f"(d[7]),
          "+f"(d[8]), "+f"(d[9]), "+f"(d[10]), "+f"(d[11]), "+f"(d[12]), "+f"(d[13]), "+f"(d[14]), "+f"(d[15]),
          "+f"(d[16]), "+f"(d[17]), "+f"(d[18]), "+f"(d[19]), "+f"(d[20]), "+f"(d[21]), "+f"(d[22]), "+f"(d[23]),
          "+f"(d[24]), "+f"(d[25]), "+f"(d[26]), "+f"(d[27]), "+f"(d[28]), "+f"(d[29]), "+f"(d[30]), "+f"(d[31]),
          "+f"(d[32]), "+f"(d[33]), "+f"(d[34]), "+f"(d[35]), "+f"(d[36]), "+f"(d[37]), "+f"(d[38]), "+f"(d[39]),
          "+f"(d[40]), "+f"(d[41]), "+f"(d[42]), "+f"(d[43]), "+f"(d[44]), "+f"(d[45]), "+f"(d[46]), "+f"(d[47])
        : "l"(da), "l"(db), "r"(scale_d), "n"(TA), "n"(TB));
}
template <int TA, int TB>
__device__ __forceinline__ void wgmma_n128_ss(float (&d)[64], uint64_t da, uint64_t db, int scale_d) {
    asm volatile("{\n.reg .pred p;\nsetp.ne.b32 p, %66, 0;\n"
        "wgmma.mma_async.sync.aligned.m64n128k16.f32.bf16.bf16 {"
        "%0, %1, %2, %3, %4, %5, %6, %7, %8, %9, %10, %11, %12, %13, %14, %15, "
        "%16, %17, %18, %19, %20, %21, %22, %23, %24, %25, %26, %27, %28, %29, %30, %31, "
        "%32, %33, %34, %35, %36, %37, %38, %39, %40, %41, %42, %43, %44, %45, %46, %47, "
        "%48, %49, %50, %51, %52, %53, %54, %55, %56, %57, %58, %59, %60, %61, %62, %63}, "
        "%64, %65, p, 1, 1, %67, %68;\n}\n"
        : "+f"(d[0]), "+f"(d[1]), "+f"(d[2]), "+f"(d[3]), "+f"(d[4]), "+f"(d[5]), "+f"(d[6]), "+f"(d[7]),
          "+f"(d[8]), "+f"(d[9]), "+f"(d[10]), "+f"(d[11]), "+f"(d[12]), "+f"(d[13]), "+f"(d[14]), "+f"(d[15]),
          "+f"(d[16]), "+f"(d[17]), "+f"(d[18]), "+f"(d[19]), "+f"(d[20]), "+f"(d[21]), "+f"(d[22]), "+f"(d[23]),
          "+f"(d[24]), "+f"(d[25]), "+f"(d[26]), "+f"(d[27]), "+f"(d[28]), "+f"(d[29]), "+f"(d[30]), "+f"(d[31]),
          "+f"(d[32]), "+f"(d[33]), "+f"(d[34]), "+f"(d[35]), "+f"(d[36]), "+f"(d[37]), "+f"(d[38]), "+f"(d[39]),
          "+f"(d[40]), "+f"(d[41]), "+f"(d[42]), "+f"(d[43]), "+f"(d[44]), "+f"(d[45]), "+f"(d[46]), "+f"(d[47]),
          "+f"(d[48]), "+f"(d[49]), "+f"(d[50]), "+f"(d[51]), "+f"(d[52]), "+f"(d[53]), "+f"(d[54]), "+f"(d[55]),
          "+f"(d[56]), "+f"(d[57]), "+f"(d[58]), "+f"(d[59]), "+f"(d[60]), "+f"(d[61]), "+f"(d[62]), "+f"(d[63])
        : "l"(da), "l"(db), "r"(scale_d), "n"(TA), "n"(TB));
}
template <int TB>
__device__ __forceinline__ void wgmma_n128_rs(float (&d)[64], uint32_t a0, uint32_t a1, uint32_t a2, uint32_t a3, uint64_t db, int scale_d) {
    asm volatile("{\n.reg .pred p;\nsetp.ne.b32 p, %69, 0;\n"
        "wgmma.mma_async.sync.aligned.m64n128k16.f32.bf16.bf16 {"
        "%0, %1, %2, %3, %4, %5, %6, %7, %8, %9, %10, %11, %12, %13, %14, %15, "
        "%16, %17, %18, %19, %20, %21, %22, %23, %24, %25, %26, %27, %28, %29, %30, %31, "
        "%32, %33, %34, %35, %36, %37, %38, %39, %40, %41, %42, %43, %44, %45, %46, %47, "
        "%48, %49, %50, %51, %52, %53, %54, %55, %56, %57, %58, %59, %60, %61, %62, %63}, "
        "{%64, %65, %66, %67}, %68, p, 1, 1, %70;\n}\n"
        : "+f"(d[0]), "+f"(d[1]), "+f"(d[2]), "+f"(d[3]), "+f"(d[4]), "+f"(d[5]), "+f"(d[6]), "+f"(d[7]),
          "+f"(d[8]), "+f"(d[9]), "+f"(d[10]), "+f"(d[11]), "+f"(d[12]), "+f"(d[13]), "+f"(d[14]), "+f"(d[15]),
          "+f"(d[16]), "+f"(d[17]), "+f"(d[18]), "+f"(d[19]), "+f"(d[20]), "+f"(d[21]), "+f"(d[22]), "+f"(d[23]),
          "+f"(d[24]), "+f"(d[25]), "+f"(d[26]), "+f"(d[27]), "+f"(d[28]), "+f"(d[29]), "+f"(d[30]), "+f"(d[31]),
          "+f"(d[32]), "+f"(d[33]), "+f"(d[34]), "+f"(d[35]), "+f"(d[36]), "+f"(d[37]), "+f"(d[38]), "+f"(d[39]),
          "+f"(d[40]), "+f"(d[41]), "+f"(d[42]), "+f"(d[43]), "+f"(d[44]), "+f"(d[45]), "+f"(d[46]), "+f"(d[47]),
          "+f"(d[48]), "+f"(d[49]), "+f"(d[50]), "+f"(d[51]), "+f"(d[52]), "+f"(d[53]), "+f"(d[54]), "+f"(d[55]),
          "+f"(d[56]), "+f"(d[57]), "+f"(d[58]), "+f"(d[59]), "+f"(d[60]), "+f"(d[61]), "+f"(d[62]), "+f"(d[63])
        : "r"(a0), "r"(a1), "r"(a2), "r"(a3), "l"(db), "r"(scale_d), "n"(TB));
}

__device__ __forceinline__ uint32_t p1_slot_off(int i) { return i == 4 ? 0 : OFF_RING + (i == 5 ? 0 : i + 1) * SLOT; }
__device__ __forceinline__ uint32_t p3_wslot_off(int i) { return OFF_RING + (i < 8 ? i + 2 : 0) * 16384; }
__device__ __forceinline__ uint32_t p3_oslot_off(int i) { return i < 3 ? i * 12288 : i == 3 ? OFF_RING + 16384 : (i - 1) * 12288; }

__device__ __forceinline__ void p1_mainloop(float (&acc0)[24], float (&acc1)[24], uint32_t sb, int wg, int lane) {
    int slot = 0, par = 0, prev = 0;
#pragma unroll 1
    for (int kb = 0; kb < 16; kb++) {
        mbar_wait(sb + OFF_BAR + (BAR_FULL1 + slot) * 8, par);
        const uint32_t st = __shfl_sync(0xffffffffu, sb + p1_slot_off(slot), 0);
        const uint64_t da = mkdesc(st + wg * 16384, 0, 1024);
        const uint64_t db = mkdesc(__shfl_sync(0xffffffffu, sb + OFF_X1 + (kb & 3) * 6144, 0), 0, 1024);
        wg_fence();
#pragma unroll
        for (int kk = 0; kk < 4; kk++) {
            wgmma_n48_ss<1, 0>(acc0, da + kk * (2048 >> 4), db + kk * (32 >> 4), (kb | kk) != 0);
            wgmma_n48_ss<1, 0>(acc1, da + (8192 >> 4) + kk * (2048 >> 4), db + kk * (32 >> 4), (kb | kk) != 0);
        }
        wg_commit();
        TLPF(threadIdx.x < 32 && (kb & 1) == 0, sb, 48 + kb / 2);
        if (kb > 0) {
            wg_wait<1>();
            if (lane == 0) mbar_arrive(sb + OFF_BAR + (BAR_EMPTY1 + prev) * 8);
        }
        prev = slot;
        if (++slot == NS1) { slot = 0; par ^= 1; }
    }
    wg_wait<0>();
    reg_fence(acc0);
    reg_fence(acc1);
    if (lane == 0) mbar_arrive(sb + OFF_BAR + (BAR_EMPTY1 + prev) * 8);
}

__device__ __forceinline__ void p3_mainloop(float (&acc)[48], uint32_t sb, int half, int lane) {
    int slot = 0, par = 0, prev = 0;
#pragma unroll 1
    for (int kb = 0; kb < 16; kb++) {
        const int ws = kb < NW3 ? kb : kb - NW3;
        mbar_wait(sb + OFF_BAR + (BAR_WFULL + ws) * 8, kb >= NW3);
        mbar_wait(sb + OFF_BAR + (BAR_OFULL + slot) * 8, par);
        const uint32_t wa = __shfl_sync(0xffffffffu, sb + p3_wslot_off(ws), 0);
        const uint32_t xa = __shfl_sync(0xffffffffu, sb + p3_oslot_off(slot), 0);
        const uint64_t da = mkdesc(wa + half * 8192, 0, 1024);
        const uint64_t db = mkdesc(xa, 0, 1024);
        wg_fence();
#pragma unroll
        for (int kk = 0; kk < 4; kk++) wgmma_n96_ss<1, 0>(acc, da + kk * (2048 >> 4), db + kk * (32 >> 4), (kb | kk) != 0);
        wg_commit();
        TLPF(threadIdx.x < 32 && (kb & 1) == 0, sb, 56 + kb / 2);
        if (kb > 0) {
            wg_wait<1>();
            if (lane == 0) mbar_arrive(sb + OFF_BAR + (BAR_EMPTY3 + prev) * 8);
        }
        prev = slot;
        if (++slot == NO3) { slot = 0; par ^= 1; }
    }
    wg_wait<0>();
    reg_fence(acc);
}

__device__ __noinline__ void attention_fallback(float* o, float* ml, uint32_t qsrc, const char* kptr, const char* vptr, int s, float c) {
    const int lane = threadIdx.x & 31;
    uint32_t q[32];
#pragma unroll
    for (int kk = 0; kk < 8; kk++) {
        const uint32_t qp = qsrc + (kk >> 2) * 8192 + (lane >> 2) * 128 + (lane & 3) * 4;
        const int c0 = (((kk & 3) * 2) ^ (lane >> 2)) << 4, c1 = (((kk & 3) * 2 + 1) ^ (lane >> 2)) << 4;
        q[4 * kk] = lds_u32(qp + c0); q[4 * kk + 1] = lds_u32(qp + 1024 + c0);
        q[4 * kk + 2] = lds_u32(qp + c1); q[4 * kk + 3] = lds_u32(qp + 1024 + c1);
    }
    float acc[64];
#pragma unroll
    for (int i = 0; i < 64; i++) acc[i] = 0.f;
    float m0 = -INFINITY, m1 = -INFINITY, l0 = 0.f, l1 = 0.f;
#pragma unroll 1
    for (int k0 = 0; k0 < 1024; k0 += 16) {
        float sc[8];
#pragma unroll
        for (int i = 0; i < 8; i++) sc[i] = 0.f;
#pragma unroll
        for (int nb = 0; nb < 2; nb++)
#pragma unroll
            for (int kk = 0; kk < 8; kk++) {
                const char* kp = kptr + (size_t)(k0 + nb * 8 + (lane >> 2)) * 256 + kk * 32 + (lane & 3) * 4;
                mma_16816(sc + 4 * nb, q[4 * kk], q[4 * kk + 1], q[4 * kk + 2], q[4 * kk + 3], *(const uint32_t*)kp, *(const uint32_t*)(kp + 16));
            }
        float n0 = fmaxf(fmaxf(sc[0], sc[1]), fmaxf(sc[4], sc[5])) * c, n1 = fmaxf(fmaxf(sc[2], sc[3]), fmaxf(sc[6], sc[7])) * c;
        n0 = fmaxf(n0, __shfl_xor_sync(0xffffffffu, n0, 1)); n1 = fmaxf(n1, __shfl_xor_sync(0xffffffffu, n1, 1));
        n0 = fmaxf(n0, __shfl_xor_sync(0xffffffffu, n0, 2)); n1 = fmaxf(n1, __shfl_xor_sync(0xffffffffu, n1, 2));
        n0 = fmaxf(n0, m0); n1 = fmaxf(n1, m1);
        const float al0 = ex2(m0 - n0), al1 = ex2(m1 - n1);
        m0 = n0; m1 = n1;
        float e[8];
#pragma unroll
        for (int i = 0; i < 8; i++) e[i] = ex2(fmaf(sc[i], c, (i & 2) ? -n1 : -n0));
        l0 = l0 * al0 + (e[0] + e[1]) + (e[4] + e[5]);
        l1 = l1 * al1 + (e[2] + e[3]) + (e[6] + e[7]);
        const uint32_t p0 = pack_bf16(e[0], e[1]), p1 = pack_bf16(e[2], e[3]), p2 = pack_bf16(e[4], e[5]), p3 = pack_bf16(e[6], e[7]);
#pragma unroll
        for (int nb = 0; nb < 16; nb++) {
            const unsigned short* vp = (const unsigned short*)(vptr + (size_t)(k0 + (lane & 3) * 2) * 256) + ((nb ^ (8 * s)) * 8) + (lane >> 2);
            const uint32_t b0 = vp[0] | ((uint32_t)vp[128] << 16), b1 = vp[8 * 128] | ((uint32_t)vp[9 * 128] << 16);
            acc[4 * nb] *= al0; acc[4 * nb + 1] *= al0; acc[4 * nb + 2] *= al1; acc[4 * nb + 3] *= al1;
            mma_16816(acc + 4 * nb, p0, p1, p2, p3, b0, b1);
        }
    }
#pragma unroll
    for (int i = 0; i < 64; i++) o[i] = acc[i];
    ml[0] = m0; ml[1] = m1; ml[2] = l0; ml[3] = l1;
}

__device__ __forceinline__ void send_stats(float m0, float m1, float& l0, float& l1, uint32_t sb, int S, int wg, int tid) {
    l0 += __shfl_xor_sync(0xffffffffu, l0, 1); l1 += __shfl_xor_sync(0xffffffffu, l1, 1);
    l0 += __shfl_xor_sync(0xffffffffu, l0, 2); l1 += __shfl_xor_sync(0xffffffffu, l1, 2);
    st_async_v4(mapa(sb + OFF_ML + tid * 16, S ^ 1), m0, m1, l0, l1, mapa(sb + OFF_BAR + (BAR_XML + wg) * 8, S ^ 1));
}

__device__ __forceinline__ void combine_and_store(float (&o)[64], float m0, float m1, float l0, float l1, uint32_t sb,
                                                  int S, int wg, int warp, int lane, int tid, int oblock) {
    constexpr int SEND = 32;
    const uint32_t wbuf = sb + OFF_Q + wg * 16384 + warp * 2048;
    const uint32_t peer_buf = mapa(wbuf + lane * 16, S ^ 1);
    const uint32_t peer_bar = mapa(sb + OFF_BAR + (BAR_XFULL + wg) * 8, S ^ 1);
#pragma unroll
    for (int q = 0; q < 4; q++) {
        const int i = SEND + 8 * q;
        st_async_v4u(peer_buf + q * 512, pack_bf16(o[i], o[i + 1]), pack_bf16(o[i + 2], o[i + 3]),
                     pack_bf16(o[i + 4], o[i + 5]), pack_bf16(o[i + 6], o[i + 7]), peer_bar);
    }
    TLPF(wg == 0 && warp == 0, sb, 45);
    mbar_wait(sb + OFF_BAR + (BAR_XML + wg) * 8, 0);
    const float4 pml = lds_v4(sb + OFF_ML + tid * 16);
    const float mm0 = fmaxf(m0, pml.x), mm1 = fmaxf(m1, pml.y);
    float a0 = ex2(m0 - mm0), b0 = ex2(pml.x - mm0);
    float a1 = ex2(m1 - mm1), b1 = ex2(pml.y - mm1);
    const float inv0 = rcp_fast(fmaf(a0, l0, b0 * pml.z)), inv1 = rcp_fast(fmaf(a1, l1, b1 * pml.w));
    a0 *= inv0; b0 *= inv0; a1 *= inv1; b1 *= inv1;
#pragma unroll
    for (int i = 0; i < 32; i++) { o[i] *= (i & 2) ? a1 : a0; asm volatile("" : "+f"(o[i])); }
    const int u = 4 * wg + warp;
    char* odst = (char*)g_oimg + (size_t)(oblock + (u / 3) * 12 + u % 3) * 2048 + lane * 16;
    const int mi = lane >> 3;
    const uint32_t ra = wbuf + 8192 + ((mi & 1) * 8 + (lane & 7)) * 128;
    mbar_wait(sb + OFF_BAR + BAR_BOK * 8, 0);
    mbar_wait(sb + OFF_BAR + (BAR_XFULL + wg) * 8, 0);
    TLPF(wg == 0 && warp == 0, sb, 46);
    float4 vf[4];
#pragma unroll
    for (int q = 0; q < 4; q++) vf[q] = lds_v4(wbuf + lane * 16 + q * 512);
#pragma unroll
    for (int q = 0; q < 4; q++) {
        const uint32_t v0 = __float_as_uint(vf[q].x), v1 = __float_as_uint(vf[q].y), v2 = __float_as_uint(vf[q].z), v3 = __float_as_uint(vf[q].w);
        const int i = 8 * q;
        stsm_x4(ra + (((2 * q + (mi >> 1)) ^ (lane & 7)) << 4),
                pack_nz(fmaf(bf_lo(v0), b0, o[i]), fmaf(bf_hi(v0), b0, o[i + 1])),
                pack_nz(fmaf(bf_lo(v1), b1, o[i + 2]), fmaf(bf_hi(v1), b1, o[i + 3])),
                pack_nz(fmaf(bf_lo(v2), b0, o[i + 4]), fmaf(bf_hi(v2), b0, o[i + 5])),
                pack_nz(fmaf(bf_lo(v3), b1, o[i + 6]), fmaf(bf_hi(v3), b1, o[i + 7])));
    }
    __syncwarp();
    TLPF(wg == 0 && warp == 0, sb, 47);
#pragma unroll
    for (int q = 0; q < 4; q++) vf[q] = lds_v4(wbuf + 8192 + q * 512 + lane * 16);
#pragma unroll
    for (int q = 0; q < 4; q++)
        st_relaxed_v4(odst + q * 512, __float_as_uint(vf[q].x), __float_as_uint(vf[q].y), __float_as_uint(vf[q].z), __float_as_uint(vf[q].w));
    __syncwarp();
    if (lane == 0) {
        fence_async_smem();
        mbar_arrive(sb + OFF_BAR + (BAR_CDONE + wg) * 8);
    }
}

template <int KB>
__device__ __forceinline__ bool tile_valid(uint32_t dst, int lane) {
    uint32_t mn = 0xffffffffu;
    const uint32_t a = dst + (lane >> 2) * 132 + (lane & 3) * 32;
#pragma unroll
    for (int i = 0; i < KB; i++) mn = min(mn, lds_u32(a + i * 1024));
    return __all_sync(0xffffffffu, mn != 0u);
}
__device__ __forceinline__ uint32_t reload_until_valid(uint32_t dst, const char* src, int kb, uint32_t tmp_bar, uint32_t tmp_par) {
    const int lane = threadIdx.x & 31;
    uint32_t mn;
    do {
        probe_wait(src + min(lane, kb / 2 - 1) * 2048 + 2044);
        if (elect_one()) {
            asm volatile("fence.acq_rel.gpu;" ::: "memory");
            fence_async_all();
            mbar_expect_tx(tmp_bar, kb * 1024);
            bulk_g2s(dst, src, kb * 1024, tmp_bar);
        }
        __syncwarp();
        mbar_wait(tmp_bar, tmp_par);
        tmp_par ^= 1;
        mn = 0xffffffffu;
#pragma unroll 1
        for (int i = 0; i < kb; i++) mn = min(mn, lds_u32(dst + (lane >> 2) * 132 + (lane & 3) * 32 + i * 1024));
    } while (!__all_sync(0xffffffffu, mn != 0u));
    return tmp_par;
}

__device__ __forceinline__ int p3_kblock(int n) { return (n >> 2) * 2 + (n & 1) + ((n >> 1) & 1) * 8; }

__device__ __forceinline__ void feed_slot(uint32_t sb, int slot, const char* oimg, int lane) {
    const uint32_t dst = sb + p3_oslot_off(slot), full = sb + OFF_BAR + (BAR_FULL3 + slot) * 8;
    uint32_t par = 0, round = 0;
#pragma unroll 1
    for (int n = slot; n < 16; n += NO3) {
        const char* src = oimg + p3_kblock(n) * 12288;
        if (n >= 4) {
            if (n >= NO3) mbar_wait(sb + OFF_BAR + (BAR_EMPTY3 + slot) * 8, round ^ 1);
            else
                for (int k = 0; k < 3; k++) mbar_wait(sb + OFF_BAR + (BAR_CDONE + k) * 8, 0);
            mbar_wait(sb + OFF_BAR + (BAR_GRP + (n >> 3)) * 8, 0);
            if (elect_one()) {
                mbar_expect_tx(full, 12288);
                bulk_g2s(dst, src, 12288, full);
            }
            __syncwarp();
        }
        mbar_wait(full, par);
        par ^= 1;
        if (!tile_valid<12>(dst, lane)) {
            par = reload_until_valid(dst, src, 12, full, par);
            TLP(lane == 0, sb, 19);
        }
        if (lane == 0) mbar_arrive(sb + OFF_BAR + (BAR_OFULL + slot) * 8);
        TLPF(lane == 0, sb, 20 + n);
        round ^= 1;
    }
}

__global__ void __cluster_dims__(2, 1, 1) __launch_bounds__(NTHREADS, 1)
gqa_fused_kernel(const __grid_constant__ CUtensorMap tm_x, const __grid_constant__ CUtensorMap tm_wq,
                 const __grid_constant__ CUtensorMap tm_k, const __grid_constant__ CUtensorMap tm_v,
                 const __grid_constant__ CUtensorMap tm_wo, const __grid_constant__ CUtensorMap tm_out,
                 __nv_bfloat16* __restrict__ out, const char* __restrict__ x, const char* __restrict__ kc,
                 const char* __restrict__ vc, const char* __restrict__ wo) {
    extern __shared__ __align__(1024) unsigned char smem[];
    uint32_t sb = smem_u32(smem);
    asm volatile("mov.u32 %0, %0;" : "+r"(sb));
    const int tid = threadIdx.x, lane = tid & 31;
    const int wg = __shfl_sync(0xffffffffu, tid >> 7, 0), warp = __shfl_sync(0xffffffffu, (tid >> 5) & 3, 0);
    if (blockIdx.x >= NCTA) {
        if (wg == 0 && elect_one()) {
            const int p = (blockIdx.x - NCTA) * 4 + warp;
            const uint32_t t0 = clock32();
#pragma unroll 1
            for (int i = 0; i < 3; i++) l2_prefetch(x + (p * 3 + i) * 16384, 16384);
#pragma unroll 1
            for (int i = 0; i < H_KV_N * 8; i++) {
                const int f = (H_SEQ >> (4 * (i >> 3))) & 15;
                while ((int)(clock32() - t0) < H_START + i * H_KV_INT) ;
                l2_prefetch(((f & 1) ? vc : kc) + (size_t)(4 * p + ((i & 7) >> 1)) * 262144 + (size_t)(f >> 1) * 32768 + (i & 1) * 16384, 16384);
            }
#pragma unroll 1
            for (int i = 0; i < 32; i++) {
                while ((int)(clock32() - t0) < H_WO_START + i * H_WO_INT) __nanosleep(100);
                l2_prefetch(wo + (size_t)(p >> 2) * 2097152 + (size_t)p3_kblock(i >> 1) * 131072 + ((p & 3) * 2 + (i & 1)) * 16384, 16384);
            }
        }
        return;
    }
    const int cl = blockIdx.x >> 1, s = blockIdx.x & 1;
    const int cls = cl < 4 ? 0 : cl < 36 ? (cl - 4) & 7 : (cl - 36) % 7 + 1;
    const int idx = cl < 4 ? 4 + cl : cl < 36 ? (cl - 4) >> 3 : 4 + (cl - 36) / 7;
    const int g = cls >> 1, tp = cls & 1;
    const int b = 4 * tp + (idx >> 1), r = idx & 1;
    const int t = 2 * tp + s;

    TL_INIT();
    if (wg == 3 && warp == 0) {
        if (elect_one()) {
            TL(0);
#pragma unroll
            for (int i = 0; i < NS1; i++) mbar_init(sb + OFF_BAR + (BAR_FULL1 + i) * 8, 1);
            fence_async_smem();
            mbar_expect_tx(sb + OFF_BAR + BAR_FULL1 * 8, 38912);
            tma_4d(sb + p1_slot_off(0), &tm_wq, 0, 0, s, g * 8 + r * 4, sb + OFF_BAR + BAR_FULL1 * 8);
            tma_2d(sb + OFF_X1, &tm_x, 0, b * 48, sb + OFF_BAR + BAR_FULL1 * 8);
            TL(1);
        }
    } else if (wg == 3 && warp == 1) {
        if (elect_one()) {
#pragma unroll
            for (int i = 0; i < NSLOT; i++) { mbar_init(sb + OFF_BAR + (BAR_FULL + i) * 8, 1); mbar_init(sb + OFF_BAR + (BAR_EMPTY + i) * 8, 12); }
#pragma unroll
            for (int i = BAR_EMPTY1; i < BAR_XFREE; i++) mbar_init(sb + OFF_BAR + i * 8, 8);
#pragma unroll
            for (int i = BAR_XFREE; i < BAR_GO2; i++) mbar_init(sb + OFF_BAR + i * 8, 4);
            mbar_init(sb + OFF_BAR + BAR_GO2 * 8, 3);
            asm volatile("fence.mbarrier_init.release.cluster;" ::: "memory");
            fence_async_smem();
        }
    } else if (wg == 3 && warp == 3) {
        if (elect_one()) {
#pragma unroll
            for (int i = BAR_ONES; i < BAR_END; i++) mbar_init(sb + OFF_BAR + i * 8, 1);
            asm volatile("fence.mbarrier_init.release.cluster;" ::: "memory");
            fence_async_smem();
        }
    } else if (wg == 3 && warp == 2) {
        if (elect_one()) { prefetch_tmap(&tm_k); prefetch_tmap(&tm_v); prefetch_tmap(&tm_wo); prefetch_tmap(&tm_out); }
    }
    __syncthreads();
    asm volatile("barrier.cluster.arrive.relaxed.aligned;" ::: "memory");

    if (wg == 3) {
        asm volatile("setmaxnreg.dec.sync.aligned.u32 32;");
        if (warp == 0) {
            if (elect_one()) {
                int i1 = 1;
#pragma unroll 1
                for (int f = 1; f < 18; f++) {
                    if (f >= NS1) mbar_wait(sb + OFF_BAR + (BAR_EMPTY1 + i1) * 8, f >= 2 * NS1);
                    const int fx = f < 4 ? f : f - 2;
                    if (f < 4 || f >= NS1) {
                        if (f < 4) mbar_expect_tx(sb + OFF_BAR + (BAR_FULL1 + i1) * 8, 38912);
                        tma_2d(sb + OFF_X1 + (fx & 3) * 6144, &tm_x, fx * 64, b * 48, sb + OFF_BAR + (BAR_FULL1 + (fx >= 12 ? fx - 12 : fx >= 6 ? fx - 6 : fx)) * 8);
                    }
                    if (f < 16) {
                        if (f >= 4) mbar_expect_tx(sb + OFF_BAR + (BAR_FULL1 + i1) * 8, 38912);
                        tma_4d(sb + p1_slot_off(i1), &tm_wq, 0, f * 64, s, g * 8 + r * 4, sb + OFF_BAR + (BAR_FULL1 + i1) * 8);
                    }
                    if (++i1 == NS1) i1 = 0;
                }
                uint32_t bar = sb + OFF_BAR, st = sb + OFF_RING;
                uint32_t par = 1;
                auto advance = [&]() {
                    bar += 8; st += SLOT;
                    if (bar == sb + OFF_BAR + NSLOT * 8) { bar = sb + OFF_BAR; st = sb + OFF_RING; par ^= 1; }
                };
                const int kvrow = (b * 4 + g) * 2048 + s * 1024;
                TL(2);
                const uint32_t tk0 = clock32();
#pragma unroll 1
                for (int f = 0; f < 16; f++) {
                    if (f == GO2_AT) mbar_arrive(sb + OFF_BAR + BAR_GO2 * 8);
                    if (f >= NSLOT) mbar_wait(bar + BAR_EMPTY * 8, par);
                    else if (f > 0) {
                        mbar_wait(sb + OFF_BAR + (BAR_EMPTY1 + f - 1) * 8, 0);
                        while ((int)(clock32() - tk0) < f * KV_GAP) ;
                    }
                    mbar_expect_tx(bar, 32768);
                    if (f & 1) {
                        tma_2d(st, &tm_v, 64 * s, kvrow + (f >> 1) * 128, bar);
                        tma_2d(st + 16384, &tm_v, 64 - 64 * s, kvrow + (f >> 1) * 128, bar);
                    } else {
                        tma_3d(st, &tm_k, 0, kvrow + (f >> 1) * 128, 0, bar);
                    }
                    advance();
                }
#pragma unroll 1
                for (int f = 0; f < NW3; f++) {
                    const uint32_t full = sb + OFF_BAR + (BAR_WFULL + f) * 8;
                    if (!(f & 1)) mbar_wait(bar + BAR_EMPTY * 8, par);
                    mbar_expect_tx(full, 16384);
                    tma_3d(st + (f & 1) * 16384, &tm_wo, 0, g * 1024 + p3_kblock(f) * 64, idx * 2, full);
                    if (f & 1) advance();
                }
#pragma unroll 1
                for (int i = 0; i < 16 - NW3; i++) {
                    const int m = min(i * WSTEP, 15 - NO3);
                    mbar_wait(sb + OFF_BAR + (BAR_EMPTY3 + (m >= NO3 ? m - NO3 : m)) * 8, m >= NO3);
                    const uint32_t wfull = sb + OFF_BAR + (BAR_WFULL + i) * 8;
                    mbar_expect_tx(wfull, 16384);
                    tma_3d(sb + p3_wslot_off(i), &tm_wo, 0, g * 1024 + p3_kblock(NW3 + i) * 64, idx * 2, wfull);
                }
                TL(6);
            }
        } else {
            const int w = warp - 1;
            if (w == 0) {
                asm volatile("barrier.cluster.wait.aligned;" ::: "memory");
                mbar_wait(sb + OFF_BAR + BAR_QFREE * 8, 0);
                const uint32_t a = sb + OFF_Q + s * 8192, pa = mapa(a, s ^ 1), pb = mapa(sb + OFF_BAR + BAR_QFULL * 8, s ^ 1);
                bar_sync_n(5, 160);
                if (elect_one()) bulk_s2peer(pa, a, 8192, pb);
                __syncwarp();
                mbar_wait(sb + OFF_BAR + (BAR_QFREE + 1) * 8, 0);
                bar_sync_n(4, 416);
                if (elect_one()) {
                    bulk_s2peer(pa + 16384, a + 16384, 8192, pb + 8);
                    bulk_s2peer(pa + 32768, a + 32768, 8192, pb + 16);
                    TL(9);
                }
            } else if (w == 2) {
                const unsigned bt = (ld_relaxed(g_bflag) / B_CNT + 1) * B_CNT;
                mbar_wait(sb + OFF_BAR + BAR_GO2 * 8, bt & 1);
#pragma unroll 1
                for (int k = 0; k < 12; k++) {
                    const int e = lane + k * 32;
                    *((uint4*)(out + (size_t)(t * 96 + g * 24 + (e >> 4)) * 1024 + idx * 128) + (e & 15)) = make_uint4(0, 0, 0, 0);
                }
                __syncwarp();
                if (elect_one()) {
                    char* oz = (char*)g_oimg + (size_t)(g * 4 + t) * 196608 + idx * 24576;
#pragma unroll 1
                    for (int k = 0; k < 6; k++) {
                        bulk_s2g(oz + k * 4096, sb + OFF_ZERO, 4096);
                        const uint32_t t1 = clock32();
                        while ((int)(clock32() - t1) < CLR_GAP) ;
                    }
                    bulk_commit();
                    bulk_wait0();
                    red_release(g_bflag, 1);
                    flag_wait(g_bflag, bt);
                    fence_async_all();
                    mbar_arrive(sb + OFF_BAR + BAR_BOK * 8);
                    TL(17);
                }
            }
            __syncwarp();
            mbar_wait(sb + OFF_BAR + BAR_BOK * 8, 0);
            const char* oimg = (const char*)g_oimg + (size_t)(g * 4 + t) * 196608;
            const char* pp = oimg + p3_kblock(min(lane, 23) / 6) * 12288 + (min(lane, 23) % 6) * 2048 + 2044;
            mbar_wait(sb + OFF_BAR + (BAR_CDONE + (w == 2)) * 8, 0);
            if (w == 2) {
                int done = 1;
#pragma unroll 1
                for (int it = 0; done < 3; it++) {
                    const unsigned v1 = ld_relaxed((const unsigned*)(pp + 24576));
                    const unsigned v2 = ld_relaxed((const unsigned*)(pp + 49152)), v3 = ld_relaxed((const unsigned*)(pp + 73728));
                    const int now = !__all_sync(0xffffffffu, v1 != 0u) ? 1 : !__all_sync(0xffffffffu, min(v2, v3) != 0u) ? 2 : 3;
                    for (; done < now; done++)
                        if (lane == 0) { mbar_arrive(sb + OFF_BAR + (BAR_GRP + done - 1) * 8); TL(36 + done); }
                    SPIN_GUARD(it)
                }
            } else {
                if (w == 0) {
                    probe_wait(pp);
                    if (elect_one()) {
                        TL(36);
#pragma unroll
                        for (int n = 0; n < 4; n++) {
                            if (n == 2) mbar_wait(sb + OFF_BAR + (BAR_CDONE + 1) * 8, 0);
                            if (n == 3) mbar_wait(sb + OFF_BAR + BAR_EMPTY * 8, 1);
                            mbar_expect_tx(sb + OFF_BAR + (BAR_FULL3 + n) * 8, 12288);
                            bulk_g2s(sb + p3_oslot_off(n), oimg + ((n & 1) + (n >> 1) * 8) * 12288, 12288, sb + OFF_BAR + (BAR_FULL3 + n) * 8);
                        }
                    }
                    __syncwarp();
                }
                feed_slot(sb, w ^ 1, oimg, lane);
            }
        }
        __syncwarp();
        if (warp != 1) asm volatile("barrier.cluster.wait.aligned;" ::: "memory");
    } else {
        asm volatile("setmaxnreg.inc.sync.aligned.u32 160;");
        const uint32_t qpiece = sb + OFF_Q + wg * 16384;
        const int mi = lane >> 3;
        if ((tid & 127) == 0) {
            mbar_expect_tx(sb + OFF_BAR + (BAR_QFULL + wg) * 8, 8192);
            mbar_expect_tx(sb + OFF_BAR + (BAR_XFULL + wg) * 8, 128 * 4 * 16);
            mbar_expect_tx(sb + OFF_BAR + (BAR_XML + wg) * 8, 128 * 16);
        }
        asm volatile("barrier.cluster.wait.aligned;" ::: "memory");
        if (wg < 2) {
            float acc0[24], acc1[24];
            p1_mainloop(acc0, acc1, sb, wg, lane);
            TLP(wg == 0 && warp == 0, sb, 8);
            mbar_wait(sb + OFF_BAR + (BAR_EMPTY1 + 4 - wg) * 8, wg ^ 1);
            const uint32_t a0 = sb + OFF_Q + s * 8192 + ((mi >> 1) * 8 + (lane & 7)) * 128 + (((2 * warp + (mi & 1)) ^ (lane & 7)) << 4);
#pragma unroll
            for (int v = 0; v < 3; v++) {
                const int u0 = 6 * wg + v, u1 = u0 + 3;
                stsm_x4_t(a0 + (u0 >> 2) * 16384 + (u0 & 3) * 2048, pack_bf16(acc0[8 * v], acc0[8 * v + 1]), pack_bf16(acc0[8 * v + 2], acc0[8 * v + 3]),
                          pack_bf16(acc0[8 * v + 4], acc0[8 * v + 5]), pack_bf16(acc0[8 * v + 6], acc0[8 * v + 7]));
                stsm_x4_t(a0 + (u1 >> 2) * 16384 + (u1 & 3) * 2048, pack_bf16(acc1[8 * v], acc1[8 * v + 1]), pack_bf16(acc1[8 * v + 2], acc1[8 * v + 3]),
                          pack_bf16(acc1[8 * v + 4], acc1[8 * v + 5]), pack_bf16(acc1[8 * v + 6], acc1[8 * v + 7]));
            }
            fence_async_smem();
            if (wg == 0) bar_sync_n(5, 160);
        } else if (warp < 2) {
            mbar_wait(sb + OFF_BAR + (BAR_EMPTY1 + 4) * 8, 0);
            mbar_wait(sb + OFF_BAR + (BAR_EMPTY1 + 4) * 8, 1);
            if (tid == 256) mbar_arrive_remote(mapa(sb + OFF_BAR + BAR_QFREE * 8, s ^ 1));
#pragma unroll
            for (int k = 0; k < 8; k++)
                asm volatile("st.shared.v4.u32 [%0], {%1, %1, %1, %1};" ::"r"(sb + OFF_ZERO + warp * 4096 + k * 512 + lane * 16), "r"(0) : "memory");
            fence_async_smem();
            __syncwarp();
            if (lane == 0) mbar_arrive(sb + OFF_BAR + BAR_GO2 * 8);
            if (warp == 0) {
                mbar_wait(sb + OFF_BAR + (BAR_EMPTY1 + 3) * 8, 0);
                if (lane == 0) mbar_arrive_remote(mapa(sb + OFF_BAR + (BAR_QFREE + 1) * 8, s ^ 1));
            }
        }
        if (wg == 0) bar_arrive_n(4, 416); else bar_sync_n(4, 416);
        TLPF(wg == 0 && warp == 0, sb, 18);

        {
            const float c = SCALE_LOG2E;
            float o[64];
            float m0 = 0.f, m1 = 0.f, l0 = 0.f, l1 = 0.f;
            bool unsafe = false;
            const uint64_t dq = mkdesc(qpiece, 0, 1024);
            mbar_wait(sb + OFF_BAR + BAR_FULL * 8, 0);
            TLPF(wg == 0 && warp == 0, sb, 16);
            auto tile = [&](auto first_c, auto last_c, const int j) {
                constexpr bool FIRST = decltype(first_c)::value, LAST = decltype(last_c)::value;
                float sc[64];
                const uint32_t kslot = (0x42031420u >> (4 * j)) & 7, vslot = (0x03142031u >> (4 * j)) & 7;
                const uint64_t dk = mkdesc(__shfl_sync(0xffffffffu, sb + OFF_RING + kslot * SLOT, 0), 0, 1024);
                if (FIRST) {
                    wg_fence();
#pragma unroll
                    for (int kk = 0; kk < 4; kk++) wgmma_n128_ss<0, 0>(sc, dq + s * (8192 >> 4) + kk * 2, dk + s * (16384 >> 4) + kk * 2, kk != 0);
                    wg_commit();
                    mbar_wait(sb + OFF_BAR + (BAR_QFULL + wg) * 8, 0);
                    TLP(warp == 0, sb, 10 + wg);
                    wg_fence();
#pragma unroll
                    for (int kk = 0; kk < 4; kk++) wgmma_n128_ss<0, 0>(sc, dq + (s ^ 1) * (8192 >> 4) + kk * 2, dk + (s ^ 1) * (16384 >> 4) + kk * 2, 1);
                    wg_commit();
                } else {
                    bar_sync_n(7 + wg, 256);
                    wg_fence();
#pragma unroll
                    for (int kk = 0; kk < 8; kk++)
                        wgmma_n128_ss<0, 0>(sc, dq + (kk >> 2) * (8192 >> 4) + (kk & 3) * 2, dk + (kk >> 2) * (16384 >> 4) + (kk & 3) * 2, kk != 0);
                    wg_commit();
                }
                { STALL_BEGIN(); mbar_wait(sb + OFF_BAR + (BAR_FULL + vslot) * 8, (0x9Cu >> j) & 1); STALL_END(8 + j); }
                wg_wait<0>();
                reg_fence(sc);
                if (lane == 0) mbar_arrive(sb + OFF_BAR + (BAR_EMPTY + kslot) * 8);
                if (FIRST) {
                    float x0 = fmaxf(sc[0], sc[1]), x1 = fmaxf(sc[2], sc[3]), y0 = fmaxf(sc[4], sc[5]), y1 = fmaxf(sc[6], sc[7]);
#pragma unroll
                    for (int i = 8; i < MAXN; i += 8) {
                        x0 = fmaxf(x0, fmaxf(sc[i], sc[i + 1])); x1 = fmaxf(x1, fmaxf(sc[i + 2], sc[i + 3]));
                        y0 = fmaxf(y0, fmaxf(sc[i + 4], sc[i + 5])); y1 = fmaxf(y1, fmaxf(sc[i + 6], sc[i + 7]));
                    }
                    x0 = fmaxf(x0, y0); x1 = fmaxf(x1, y1);
                    x0 = fmaxf(x0, __shfl_xor_sync(0xffffffffu, x0, 1)); x1 = fmaxf(x1, __shfl_xor_sync(0xffffffffu, x1, 1));
                    x0 = fmaxf(x0, __shfl_xor_sync(0xffffffffu, x0, 2)); x1 = fmaxf(x1, __shfl_xor_sync(0xffffffffu, x1, 2));
                    m0 = x0 * c; m1 = x1 * c;
                }
                uint32_t p[32];
                const uint64_t dv = mkdesc(__shfl_sync(0xffffffffu, sb + OFF_RING + vslot * SLOT, 0), 16384, 1024);
#pragma unroll
                for (int ch = 0; ch < NCHK; ch++) {
                    const int k0 = (CHB >> (4 * ch)) & 15, k1 = (CHB >> (4 * ch + 4)) & 15;
#pragma unroll
                    for (int i = 2 * k0; i < 2 * k1; i++) {
                        const float e0 = ex2(fmaf(sc[4 * i], c, -m0)), e1 = ex2(fmaf(sc[4 * i + 1], c, -m0));
                        const float e2 = ex2(fmaf(sc[4 * i + 2], c, -m1)), e3 = ex2(fmaf(sc[4 * i + 3], c, -m1));
                        p[2 * i] = pack_bf16(e0, e1);
                        p[2 * i + 1] = pack_bf16(e2, e3);
                    }
                    wg_fence();
#pragma unroll
                    for (int kk = k0; kk < k1; kk++)
                        wgmma_n128_rs<1>(o, p[4 * kk], p[4 * kk + 1], p[4 * kk + 2], p[4 * kk + 3], dv + kk * (2048 >> 4), (!FIRST || kk != 0));
                    wg_commit();
                    if (ch == (LAST ? ARR_L : ARR_CH)) {
                        if (FIRST && wg == 2) bar_sync_n(10, 256);
                        if (wg == 0 || !LAST) bar_arrive_n(wg == 0 ? (FIRST ? 10 : 9) : 6 + wg, 256);
                    }
                }
#pragma unroll
                for (int h = 0; h < 2; h++) {
                    const uint32_t* q = p + h * 16;
                    const uint32_t a = hadd2(hadd2(hadd2(q[0], q[2]), hadd2(q[4], q[6])), hadd2(hadd2(q[8], q[10]), hadd2(q[12], q[14])));
                    const uint32_t d = hadd2(hadd2(hadd2(q[1], q[3]), hadd2(q[5], q[7])), hadd2(hadd2(q[9], q[11]), hadd2(q[13], q[15])));
                    l0 += bf_lo(a) + bf_hi(a);
                    l1 += bf_lo(d) + bf_hi(d);
                }
                if (!LAST) {
                    STALL_BEGIN(); mbar_wait(sb + OFF_BAR + (BAR_FULL + ((0x04203142u >> (4 * j)) & 7)) * 8, (0x0Cu >> j) & 1); STALL_END(j + 1);
                } else {
                    unsafe = __any_sync(0xffffffffu, !(l0 <= L_SAFE && l1 <= L_SAFE));
                    if (!unsafe) {
                        if (lane == 0) mbar_arrive_remote(mapa(sb + OFF_BAR + (BAR_XFREE + wg) * 8, s ^ 1));
                        send_stats(m0, m1, l0, l1, sb, s, wg, tid);
                    }
                }
                wg_wait<0>();
                reg_fence(o);
                if (lane == 0) mbar_arrive(sb + OFF_BAR + (BAR_EMPTY + vslot) * 8);
            };
            tile(Int<1>{}, Int<0>{}, 0);
#pragma unroll 1
            for (int jj = 1; jj < 7; jj++) tile(Int<0>{}, Int<0>{}, __shfl_sync(0xffffffffu, jj, 0));
            tile(Int<0>{}, Int<1>{}, 7);
            TLP(warp == 0, sb, 42 + wg);
            if (unsafe) {
                float fo[64], fml[4];
                const size_t kvoff = (size_t)((b * 4 + g) * 2048 + s * 1024) * 256;
                attention_fallback(fo, fml, qpiece + warp * 2048, kc + kvoff, vc + kvoff, s, c);
#pragma unroll
                for (int i = 0; i < 64; i++) o[i] = fo[i];
                m0 = fml[0]; m1 = fml[1]; l0 = fml[2]; l1 = fml[3];
                if (lane == 0) mbar_arrive_remote(mapa(sb + OFF_BAR + (BAR_XFREE + wg) * 8, s ^ 1));
                send_stats(m0, m1, l0, l1, sb, s, wg, tid);
            }
            mbar_wait(sb + OFF_BAR + (BAR_XFREE + wg) * 8, 0);
            const int oblock = ((g * 4 + (b >> 1)) * 16 + 8 * r + s) * 6 + (b & 1) * 3;
            combine_and_store(o, m0, m1, l0, l1, sb, s, wg, warp, lane, tid, oblock);
            TLP(warp == 0, sb, 13 + wg);
        }

        if (wg < 2) {
            float acc[48];
            p3_mainloop(acc, sb, wg, lane);
            TLP(wg == 0 && warp == 0, sb, 40);
            named_sync(1 + wg);
            const uint32_t stg = sb + p3_wslot_off(14 - NW3) + wg * 8192;
            const uint32_t a0 = stg + ((mi >> 1) * 8 + (lane & 7)) * 128 + (((2 * warp + (mi & 1)) ^ (lane & 7)) << 4);
#pragma unroll
            for (int j = 0; j < 12; j += 2)
                stsm_x4_t(a0 + (j / 6) * 16384 + (j % 6) * 1024, pack_bf16(acc[4 * j], acc[4 * j + 1]), pack_bf16(acc[4 * j + 2], acc[4 * j + 3]),
                          pack_bf16(acc[4 * j + 4], acc[4 * j + 5]), pack_bf16(acc[4 * j + 6], acc[4 * j + 7]));
            fence_async_smem();
            named_sync(1 + wg);
            if (warp == 0 && elect_one()) {
                tma_reduce_add_2d(&tm_out, idx * 128 + wg * 64, t * 96, stg);
                tma_reduce_add_2d(&tm_out, idx * 128 + wg * 64, t * 96 + 48, stg + 16384);
                bulk_commit();
                bulk_wait0_read();
                TLP(wg == 0, sb, 41);
            }
            __syncwarp();
            TL_DONE();
        } else {
            feed_slot(sb, 2 + warp, (const char*)g_oimg + (size_t)(g * 4 + t) * 196608, lane);
            TL_DONE();
        }
    }
}

typedef CUresult (*EncodeFn)(CUtensorMap*, CUtensorMapDataType, cuuint32_t, void*, const cuuint64_t*, const cuuint64_t*,
                             const cuuint32_t*, const cuuint32_t*, CUtensorMapInterleave, CUtensorMapSwizzle,
                             CUtensorMapL2promotion, CUtensorMapFloatOOBfill);

void make_map(EncodeFn enc, CUtensorMap* m, const void* ptr, int rank, uint64_t rows, uint64_t cols, uint32_t box_rows, int promo = 3) {
    cuuint64_t dims[3] = {rank == 2 ? cols : 64, rows, cols / 64};
    cuuint64_t strides[2] = {cols * 2, 128};
    cuuint32_t box[3] = {64, box_rows, 2};
    cuuint32_t es[3] = {1, 1, 1};
    enc(m, CU_TENSOR_MAP_DATA_TYPE_BFLOAT16, rank, const_cast<void*>(ptr), dims, strides, box, es, CU_TENSOR_MAP_INTERLEAVE_NONE,
        CU_TENSOR_MAP_SWIZZLE_128B, (CUtensorMapL2promotion)promo, CU_TENSOR_MAP_FLOAT_OOB_FILL_NONE);
}

}

extern "C" void kernel_launch(void* const* d_in, const int* in_sizes, int n_in, void* d_out, int out_size) {
    (void)in_sizes; (void)n_in; (void)out_size;
    static EncodeFn enc = nullptr;
    static int grid = NCTA;
    if (!enc) {
        void* fn = nullptr;
        cudaDriverEntryPointQueryResult qr;
        cudaGetDriverEntryPoint("cuTensorMapEncodeTiled", &fn, cudaEnableDefault, &qr);
        enc = (EncodeFn)fn;
        cudaFuncSetAttribute(gqa_fused_kernel, cudaFuncAttributeMaxDynamicSharedMemorySize, SMEM_TOTAL);
        cudaLaunchConfig_t cfg = {};
        cfg.gridDim = dim3(NCTA + 4);
        cfg.blockDim = dim3(NTHREADS);
        cfg.dynamicSmemBytes = SMEM_TOTAL;
        cudaLaunchAttribute at;
        at.id = cudaLaunchAttributeClusterDimension;
        at.val.clusterDim.x = 2; at.val.clusterDim.y = 1; at.val.clusterDim.z = 1;
        cfg.attrs = &at;
        cfg.numAttrs = 1;
        int ncl = 0;
        if (cudaOccupancyMaxActiveClusters(&ncl, gqa_fused_kernel, &cfg) == cudaSuccess && ncl >= NCTA / 2 + 2) grid = NCTA + 4;
        (void)cudaGetLastError();
    }
    CUtensorMap tx, twq, tk, tv, two, tout;
    make_map(enc, &tx, d_in[0], 2, 384, 1024, 48);
    make_map(enc, &tk, d_in[1], 3, 65536, 128, 128, PROMO_KV);
    make_map(enc, &tv, d_in[2], 2, 65536, 128, 128, PROMO_KV);
    {
        cuuint64_t dims[4] = {64, 1024, 2, 32};
        cuuint64_t strides[3] = {8192, 128, 256};
        cuuint32_t box[4] = {64, 64, 1, 4};
        cuuint32_t es[4] = {1, 1, 1, 1};
        enc(&twq, CU_TENSOR_MAP_DATA_TYPE_BFLOAT16, 4, d_in[3], dims, strides, box, es, CU_TENSOR_MAP_INTERLEAVE_NONE,
            CU_TENSOR_MAP_SWIZZLE_128B, (CUtensorMapL2promotion)PROMO_W, CU_TENSOR_MAP_FLOAT_OOB_FILL_NONE);
    }
    make_map(enc, &two, d_in[4], 3, 4096, 1024, 64);
    make_map(enc, &tout, d_out, 2, 384, 1024, 48);
    gqa_fused_kernel<<<grid, NTHREADS, SMEM_TOTAL, cudaStreamPerThread>>>(tx, twq, tk, tv, two, tout, (__nv_bfloat16*)d_out,
        (const char*)d_in[0], (const char*)d_in[1], (const char*)d_in[2], (const char*)d_in[4]);
}
```
